```python
import torch

def _softmax(x, axis=-1):
    return torch.softmax(x, dim=axis)
def _gelu(x):
    return torch.nn.functional.gelu(x, approximate="tanh")
def _silu(x):
    return torch.nn.functional.silu(x)
def _sigmoid(x):
    return torch.sigmoid(x)
def _layernorm(x, axis=-1, eps=1e-5):
    m = x.mean(dim=axis, keepdim=True)
    v = x.var(dim=axis, keepdim=True, unbiased=False)
    return (x - m) / torch.sqrt(v + eps)
def _scatter_add(tgt, idx, src, axis=0):
    return tgt.clone().index_add_(axis, idx, src)
def _segment_sum(src, seg, n):
    out = torch.zeros((n,) + src.shape[1:], dtype=src.dtype)
    return out.index_add_(0, seg, src)
def _pad(x, pw):
    flat = tuple(v for pair in reversed(pw) for v in pair)
    return torch.nn.functional.pad(x, flat)

kernel_name = 'sequential_preLN__compressed_kv_cla__glu_gated_glu__prompt'

def setup_inputs():

    _w = (lambda a: (lambda t: t.to(torch.bfloat16) if t.is_floating_point() else t)(torch.as_tensor(a)))
    def _A_setup():
        B, H, Sq, Sk, D, M = 1, 32, 2048, 2048, 128, 512
        Dc = 4 * D
        return {
            "x": _w((lambda *s: torch.randn(*s, dtype=torch.bfloat16) * 0.05)(B, Sq, M)),
            "c_kv": _w((lambda *s: torch.randn(*s, dtype=torch.bfloat16) * 0.4)(B, Sk, Dc)),
            "w_q": _w((lambda *s: torch.randn(*s, dtype=torch.bfloat16) * 3.2)(M, H, D) * (M ** -0.5)),
            "w_uk": _w((lambda *s: torch.randn(*s, dtype=torch.bfloat16) * 3.2)(Dc, H, D) * (Dc ** -0.5)),
            "w_uv": _w((lambda *s: torch.randn(*s, dtype=torch.bfloat16) * 0.4)(Dc, H, D) * (Dc ** -0.5)),
            "w_o": _w((lambda *s: torch.randn(*s, dtype=torch.bfloat16) * 0.4)(H, D, M) * ((H * D) ** -0.5)),
        }
    _A_in = _A_setup()

    def _B_setup():
        B, S, D, F = 1, 2048, 512, 1792
        return {
            "x": _w((lambda *s: torch.randn(*s, dtype=torch.bfloat16) * 0.05)(B, S, D)),
            "w_gate": _w((lambda *s: torch.randn(*s, dtype=torch.bfloat16) * 0.05)(D, F)),
            "w_up": _w((lambda *s: torch.randn(*s, dtype=torch.bfloat16) * 0.05)(D, F)),
            "w_down": _w((lambda *s: torch.randn(*s, dtype=torch.bfloat16) * 0.05)(F, D)),
        }
    _B_in = _B_setup()

    return {
        "A_x": _A_in["x"],
        "A_c_kv": _A_in["c_kv"],
        "A_w_q": _A_in["w_q"],
        "A_w_uk": _A_in["w_uk"],
        "A_w_uv": _A_in["w_uv"],
        "A_w_o": _A_in["w_o"],
        "B_x": _B_in["x"],
        "B_w_gate": _B_in["w_gate"],
        "B_w_up": _B_in["w_up"],
        "B_w_down": _B_in["w_down"],
    }

def reference(A_x, A_c_kv, A_w_q, A_w_uk, A_w_uv, A_w_o, B_x, B_w_gate, B_w_up, B_w_down):
    def _A_ref(x, c_kv, w_q, w_uk, w_uv, w_o):
        B, Sq, M = x.shape[0], x.shape[1], x.shape[2]
        Sk = c_kv.shape[1]
        H, D = w_q.shape[1], w_q.shape[2]
        q = torch.einsum("bqm,mhd->bhqd", x, w_q)
        k = torch.einsum("bkc,chd->bhkd", c_kv, w_uk)
        v = torch.einsum("bkc,chd->bhkd", c_kv, w_uv)
        scores = torch.einsum("bhqd,bhkd->bhqk", q, k) * (D ** -0.5)
        off = Sk - Sq
        qi = torch.arange(Sq)[:, None]
        kj = torch.arange(Sk)[None, :]
        cmask = kj <= (qi + off)
        scores = torch.where(cmask[None, None], scores, -1e9)
        p = _softmax(scores, axis=-1)
        ctx = torch.einsum("bhqk,bhkd->bhqd", p, v)
        return torch.einsum("bhqd,hdm->bqm", ctx, w_o)

    def _B_ref(x, w_gate, w_up, w_down):
        g = torch.einsum("bsd,df->bsf", x, w_gate)
        u = torch.einsum("bsd,df->bsf", x, w_up)
        h = _sigmoid(g) * u
        return torch.einsum("bsf,fd->bsd", h, w_down)

    x = A_x
    h = x + _A_ref(_layernorm(x, axis=-1), A_c_kv, A_w_q, A_w_uk, A_w_uv, A_w_o)
    h2 = h + _B_ref(_layernorm(h, axis=-1), B_w_gate, B_w_up, B_w_down)
    return h2
```

```cpp
#include <cuda_runtime.h>
#include <cuda_bf16.h>
#include <cuda.h>
#include <stdint.h>

constexpr int SEQ = 2048, DM = 512, NH = 32, HD = 128, HDALL = 4096, FF = 1792;

__device__ __forceinline__ uint32_t smem_u32(const void* p) { return (uint32_t)__cvta_generic_to_shared(p); }
__device__ __forceinline__ void mbar_init(uint32_t bar, uint32_t count) {
  asm volatile("mbarrier.init.shared::cta.b64 [%0], %1;" :: "r"(bar), "r"(count) : "memory");
}
__device__ __forceinline__ void mbar_expect_tx(uint32_t bar, uint32_t bytes) {
  asm volatile("mbarrier.arrive.expect_tx.shared::cta.b64 _, [%0], %1;" :: "r"(bar), "r"(bytes) : "memory");
}
__device__ __forceinline__ void mbar_arrive(uint32_t bar) {
  asm volatile("mbarrier.arrive.shared::cta.b64 _, [%0];" :: "r"(bar) : "memory");
}

#define SPIN_LIMIT "2000000"
#define SPIN_DBG(IDOP, VALOP)
template<int ID> __device__ __forceinline__ void mbar_wait(uint32_t bar, uint32_t parity) {
  asm volatile("{\n.reg .pred p;\n.reg .u32 c;\nmov.u32 c, 0;\n"
    "LAB_WAIT:\n"
    "mbarrier.try_wait.parity.shared::cta.b64 p, [%0], %1;\n"
    "@p bra LAB_DONE;\n"
    "add.u32 c, c, 1;\n"
    SPIN_DBG("%2", "%1")
    "setp.gt.u32 p, c, " SPIN_LIMIT ";\n"
    "@p trap;\n"
    "bra LAB_WAIT;\n"
    "LAB_DONE:\n}" :: "r"(bar), "r"(parity), "n"(ID) : "memory");
}
__device__ __forceinline__ void tma_load_2d(uint32_t dst, const CUtensorMap* m, uint32_t bar, int c0, int c1) {
  asm volatile("cp.async.bulk.tensor.2d.shared::cluster.global.mbarrier::complete_tx::bytes [%0], [%1, {%3, %4}], [%2];"
    :: "r"(dst), "l"(m), "r"(bar), "r"(c0), "r"(c1) : "memory");
}
__device__ __forceinline__ void tma_load_3d(uint32_t dst, const CUtensorMap* m, uint32_t bar, int c0, int c1, int c2) {
  asm volatile("cp.async.bulk.tensor.3d.shared::cluster.global.mbarrier::complete_tx::bytes [%0], [%1, {%3, %4, %5}], [%2];"
    :: "r"(dst), "l"(m), "r"(bar), "r"(c0), "r"(c1), "r"(c2) : "memory");
}
__device__ __forceinline__ void tma_load_5d(uint32_t dst, const CUtensorMap* m, uint32_t bar, int c0, int c1, int c2, int c3, int c4) {
  asm volatile("cp.async.bulk.tensor.5d.shared::cluster.global.mbarrier::complete_tx::bytes [%0], [%1, {%3, %4, %5, %6, %7}], [%2];"
    :: "r"(dst), "l"(m), "r"(bar), "r"(c0), "r"(c1), "r"(c2), "r"(c3), "r"(c4) : "memory");
}
__device__ __forceinline__ void prefetch_tmap(const CUtensorMap* m) {
  asm volatile("prefetch.tensormap [%0];" :: "l"(m) : "memory");
}
__device__ __forceinline__ void wgmma_fence() { asm volatile("wgmma.fence.sync.aligned;" ::: "memory"); }
__device__ __forceinline__ void wgmma_commit() { asm volatile("wgmma.commit_group.sync.aligned;" ::: "memory"); }
template<int N> __device__ __forceinline__ void wgmma_wait() { asm volatile("wgmma.wait_group.sync.aligned %0;" :: "n"(N) : "memory"); }
template<int R> __device__ __forceinline__ void reg_alloc() { asm volatile("setmaxnreg.inc.sync.aligned.u32 %0;" :: "n"(R)); }
template<int R> __device__ __forceinline__ void reg_dealloc() { asm volatile("setmaxnreg.dec.sync.aligned.u32 %0;" :: "n"(R)); }
__device__ __forceinline__ void named_bar_sync(int id, int n) { asm volatile("bar.sync %0, %1;" :: "r"(id), "r"(n) : "memory"); }
__device__ __forceinline__ void named_bar_arrive(int id, int n) { asm volatile("bar.arrive %0, %1;" :: "r"(id), "r"(n) : "memory"); }
__device__ __forceinline__ uint64_t make_desc(uint32_t addr, uint32_t lbo_bytes, uint32_t sbo_bytes) {
  uint64_t d = 0;
  d |= (uint64_t)((addr & 0x3FFFF) >> 4);
  d |= (uint64_t)(lbo_bytes >> 4) << 16;
  d |= (uint64_t)(sbo_bytes >> 4) << 32;
  d |= (uint64_t)1 << 62;
  return d;
}
__device__ __forceinline__ uint32_t desc_lo(uint32_t addr, uint32_t lbo_bytes) { return ((addr & 0x3FFFF) >> 4) + ((lbo_bytes >> 4) << 16); }
template<int N> __device__ __forceinline__ void fence_regs(float (&d)[N]) {
#pragma unroll
  for (int i = 0; i < N; i++) asm volatile("" : "+f"(d[i]) :: "memory");
}
template<int N> __device__ __forceinline__ void fence_regs(uint32_t (&d)[N]) {
#pragma unroll
  for (int i = 0; i < N; i++) asm volatile("" : "+r"(d[i]) :: "memory");
}
__device__ __forceinline__ uint32_t pack_bf16(float lo, float hi) {
  uint32_t r; asm("cvt.rn.bf16x2.f32 %0, %1, %2;" : "=r"(r) : "f"(hi), "f"(lo)); return r;
}
__device__ __forceinline__ float ex2(float x) { float y; asm("ex2.approx.ftz.f32 %0, %1;" : "=f"(y) : "f"(x)); return y; }
__device__ __forceinline__ float bf16lo(uint32_t v) { return __uint_as_float(v << 16); }
__device__ __forceinline__ float bf16hi(uint32_t v) { return __uint_as_float(v & 0xffff0000u); }

__device__ __forceinline__ uint32_t mapa(uint32_t addr, uint32_t cta) {
  uint32_t r; asm("mapa.shared::cluster.u32 %0, %1, %2;" : "=r"(r) : "r"(addr), "r"(cta)); return r;
}
__device__ __forceinline__ void mbar_arrive_cl(uint32_t cluster_addr) {
  asm volatile("mbarrier.arrive.shared::cluster.b64 _, [%0];" :: "r"(cluster_addr) : "memory");
}
template<int ID> __device__ __forceinline__ void mbar_wait_cl(uint32_t bar, uint32_t parity) {
  asm volatile("{\n.reg .pred p;\n.reg .u32 c;\nmov.u32 c, 0;\n"
    "LAB_WAIT:\n"
    "mbarrier.try_wait.parity.acquire.cluster.shared::cta.b64 p, [%0], %1;\n"
    "@p bra LAB_DONE;\n"
    "add.u32 c, c, 1;\n"
    SPIN_DBG("%2", "%1")
    "setp.gt.u32 p, c, " SPIN_LIMIT ";\n"
    "@p trap;\n"
    "bra LAB_WAIT;\n"
    "LAB_DONE:\n}" :: "r"(bar), "r"(parity), "n"(ID) : "memory");
}
__device__ __forceinline__ void tma_load_2d_mc(uint32_t dst, const CUtensorMap* m, uint32_t bar, int c0, int c1) {
  asm volatile("cp.async.bulk.tensor.2d.shared::cluster.global.mbarrier::complete_tx::bytes.multicast::cluster [%0], [%1, {%3, %4}], [%2], %5;"
    :: "r"(dst), "l"(m), "r"(bar), "r"(c0), "r"(c1), "h"((uint16_t)3) : "memory");
}
__device__ __forceinline__ void tma_load_3d_mc(uint32_t dst, const CUtensorMap* m, uint32_t bar, int c0, int c1, int c2) {
  asm volatile("cp.async.bulk.tensor.3d.shared::cluster.global.mbarrier::complete_tx::bytes.multicast::cluster [%0], [%1, {%3, %4, %5}], [%2], %6;"
    :: "r"(dst), "l"(m), "r"(bar), "r"(c0), "r"(c1), "r"(c2), "h"((uint16_t)3) : "memory");
}
__device__ __forceinline__ void tma_store_2d(const CUtensorMap* m, uint32_t src, int c0, int c1) {
  asm volatile("cp.async.bulk.tensor.2d.global.shared::cta.bulk_group [%0, {%2, %3}], [%1];" :: "l"(m), "r"(src), "r"(c0), "r"(c1) : "memory");
}
__device__ __forceinline__ void tma_store_3d(const CUtensorMap* m, uint32_t src, int c0, int c1, int c2) {
  asm volatile("cp.async.bulk.tensor.3d.global.shared::cta.bulk_group [%0, {%2, %3, %4}], [%1];" :: "l"(m), "r"(src), "r"(c0), "r"(c1), "r"(c2) : "memory");
}
__device__ __forceinline__ void bulk_store(void* gdst, uint32_t src, uint32_t bytes) {
  asm volatile("cp.async.bulk.global.shared::cta.bulk_group [%0], [%1], %2;" :: "l"(gdst), "r"(src), "r"(bytes) : "memory");
}
__device__ __forceinline__ void bulk_load(uint32_t dst, const void* gsrc, uint32_t bytes, uint32_t bar) {
  asm volatile("cp.async.bulk.shared::cluster.global.mbarrier::complete_tx::bytes [%0], [%1], %2, [%3];" :: "r"(dst), "l"(gsrc), "r"(bytes), "r"(bar) : "memory");
}
__device__ __forceinline__ void prefetch_3d(const CUtensorMap* m, int c0, int c1, int c2) {
  asm volatile("cp.async.bulk.prefetch.tensor.3d.L2.global [%0, {%1, %2, %3}];" :: "l"(m), "r"(c0), "r"(c1), "r"(c2) : "memory");
}
__device__ __forceinline__ void prefetch_2d(const CUtensorMap* m, int c0, int c1) {
  asm volatile("cp.async.bulk.prefetch.tensor.2d.L2.global [%0, {%1, %2}];" :: "l"(m), "r"(c0), "r"(c1) : "memory");
}
__device__ __forceinline__ void bulk_commit() { asm volatile("cp.async.bulk.commit_group;" ::: "memory"); }
__device__ __forceinline__ void bulk_wait_read() { asm volatile("cp.async.bulk.wait_group.read 0;" ::: "memory"); }
__device__ __forceinline__ void bulk_wait_all() { asm volatile("cp.async.bulk.wait_group 0;" ::: "memory"); }
__device__ __forceinline__ void fence_async_smem() { asm volatile("fence.proxy.async.shared::cta;" ::: "memory"); }
__device__ __forceinline__ void stmatrix_x4(uint32_t addr, uint32_t a, uint32_t b, uint32_t c, uint32_t d) {
  asm volatile("stmatrix.sync.aligned.m8n8.x4.shared.b16 [%0], {%1, %2, %3, %4};" :: "r"(addr), "r"(a), "r"(b), "r"(c), "r"(d) : "memory");
}
__device__ __forceinline__ void st_async_v4(uint32_t raddr, float a, float b, float c, float d, uint32_t rbar) {
  asm volatile("st.async.weak.shared::cluster.mbarrier::complete_tx::bytes.v4.f32 [%0], {%1, %2, %3, %4}, [%5];"
    :: "r"(raddr), "f"(a), "f"(b), "f"(c), "f"(d), "r"(rbar) : "memory");
}
__device__ __forceinline__ float4 lds_v4(uint32_t addr) {
  float4 v; asm volatile("ld.shared.v4.f32 {%0, %1, %2, %3}, [%4];" : "=f"(v.x), "=f"(v.y), "=f"(v.z), "=f"(v.w) : "r"(addr) : "memory"); return v;
}
__device__ __forceinline__ float2 lds_v2(uint32_t addr) {
  float2 v; asm volatile("ld.shared.v2.f32 {%0, %1}, [%2];" : "=f"(v.x), "=f"(v.y) : "r"(addr) : "memory"); return v;
}
__device__ __forceinline__ void sts_v2(uint32_t addr, float a, float b) {
  asm volatile("st.shared.v2.f32 [%0], {%1, %2};" :: "r"(addr), "f"(a), "f"(b) : "memory");
}
__device__ __forceinline__ void flag_arrive(uint32_t* p) {
  asm volatile("red.release.gpu.global.add.u32 [%0], 1;" :: "l"(p) : "memory");
}
__device__ __forceinline__ void flag_arrive_relaxed(uint32_t* p) {
  asm volatile("red.relaxed.gpu.global.add.u32 [%0], 1;" :: "l"(p) : "memory");
}
template<int ID> __device__ __forceinline__ void flag_wait_relaxed(const uint32_t* p, uint32_t target) {
  asm volatile("{\n.reg .pred p;\n.reg .u32 c, v;\nmov.u32 c, 0;\n"
    "LAB_WAIT:\n"
    "ld.relaxed.gpu.global.u32 v, [%0];\n"
    "sub.u32 v, v, %1;\n"
    "setp.ge.s32 p, v, 0;\n"
    "@p bra LAB_DONE;\n"
    "add.u32 c, c, 1;\n"
    SPIN_DBG("%2", "v")
    "setp.gt.u32 p, c, " SPIN_LIMIT ";\n"
    "@p trap;\n"
    "bra LAB_WAIT;\n"
    "LAB_DONE:\n}" :: "l"(p), "r"(target), "n"(ID) : "memory");
}
template<int ID> __device__ __forceinline__ void flag_wait(const uint32_t* p, uint32_t target) {
  asm volatile("{\n.reg .pred p;\n.reg .u32 c, v;\nmov.u32 c, 0;\n"
    "LAB_WAIT:\n"
    "ld.acquire.gpu.global.u32 v, [%0];\n"
    "sub.u32 v, v, %1;\n"
    "setp.ge.s32 p, v, 0;\n"
    "@p bra LAB_DONE;\n"
    "add.u32 c, c, 1;\n"
    SPIN_DBG("%2", "v")
    "setp.gt.u32 p, c, " SPIN_LIMIT ";\n"
    "@p trap;\n"
    "bra LAB_WAIT;\n"
    "LAB_DONE:\n"
    "fence.proxy.async;\n}" :: "l"(p), "r"(target), "n"(ID) : "memory");
}
__device__ __forceinline__ void mbar_expect_only(uint32_t bar, uint32_t bytes) {
  asm volatile("mbarrier.expect_tx.relaxed.cta.shared::cta.b64 [%0], %1;" :: "r"(bar), "r"(bytes) : "memory");
}
__device__ __forceinline__ void prefetch_l2(const void* p, uint32_t bytes) {
  asm volatile("cp.async.bulk.prefetch.L2.global [%0], %1;" :: "l"(p), "r"(bytes) : "memory");
}
__device__ __forceinline__ void cluster_arrive() { asm volatile("barrier.cluster.arrive.release.aligned;" ::: "memory"); }
__device__ __forceinline__ void cluster_wait() { asm volatile("barrier.cluster.wait.acquire.aligned;" ::: "memory"); }

#define PROF_T(k, i)
#define PROF_G(k, i)
template<int TB> __device__ __forceinline__ void wgmma_m64n128k16_ss(float (&d)[64], uint32_t da, uint32_t db, int scale_d) {
  asm volatile("{\n.reg .pred p;\n.reg .b64 da, db;\nsetp.ne.b32 p, %66, 0;\nmov.b64 da, {%64, 0x40000040};\nmov.b64 db, {%65, 0x40000040};\n"
    "wgmma.mma_async.sync.aligned.m64n128k16.f32.bf16.bf16 "
    "{%0, %1, %2, %3, %4, %5, %6, %7, %8, %9, %10, %11, %12, %13, %14, %15, "
    "%16, %17, %18, %19, %20, %21, %22, %23, %24, %25, %26, %27, %28, %29, %30, %31, "
    "%32, %33, %34, %35, %36, %37, %38, %39, %40, %41, %42, %43, %44, %45, %46, %47, "
    "%48, %49, %50, %51, %52, %53, %54, %55, %56, %57, %58, %59, %60, %61, %62, %63}, "
    "da, db, p, 1, 1, 0, %67;\n}\n"
    : "+f"(d[0]), "+f"(d[1]), "+f"(d[2]), "+f"(d[3]), "+f"(d[4]), "+f"(d[5]), "+f"(d[6]), "+f"(d[7]), "+f"(d[8]), "+f"(d[9]), "+f"(d[10]), "+f"(d[11]), "+f"(d[12]), "+f"(d[13]), "+f"(d[14]), "+f"(d[15]), "+f"(d[16]), "+f"(d[17]), "+f"(d[18]), "+f"(d[19]), "+f"(d[20]), "+f"(d[21]), "+f"(d[22]), "+f"(d[23]), "+f"(d[24]), "+f"(d[25]), "+f"(d[26]), "+f"(d[27]), "+f"(d[28]), "+f"(d[29]), "+f"(d[30]), "+f"(d[31]), "+f"(d[32]), "+f"(d[33]), "+f"(d[34]), "+f"(d[35]), "+f"(d[36]), "+f"(d[37]), "+f"(d[38]), "+f"(d[39]), "+f"(d[40]), "+f"(d[41]), "+f"(d[42]), "+f"(d[43]), "+f"(d[44]), "+f"(d[45]), "+f"(d[46]), "+f"(d[47]), "+f"(d[48]), "+f"(d[49]), "+f"(d[50]), "+f"(d[51]), "+f"(d[52]), "+f"(d[53]), "+f"(d[54]), "+f"(d[55]), "+f"(d[56]), "+f"(d[57]), "+f"(d[58]), "+f"(d[59]), "+f"(d[60]), "+f"(d[61]), "+f"(d[62]), "+f"(d[63])
    : "r"(da), "r"(db), "r"(scale_d), "n"(TB));
}
template<int TB> __device__ __forceinline__ void wgmma_m64n128k16_rs(float (&d)[64], uint32_t a0, uint32_t a1, uint32_t a2, uint32_t a3, uint32_t db, int scale_d) {
  asm volatile("{\n.reg .pred p;\n.reg .b64 db;\nsetp.ne.b32 p, %69, 0;\nmov.b64 db, {%68, 0x40000040};\n"
    "wgmma.mma_async.sync.aligned.m64n128k16.f32.bf16.bf16 "
    "{%0, %1, %2, %3, %4, %5, %6, %7, %8, %9, %10, %11, %12, %13, %14, %15, "
    "%16, %17, %18, %19, %20, %21, %22, %23, %24, %25, %26, %27, %28, %29, %30, %31, "
    "%32, %33, %34, %35, %36, %37, %38, %39, %40, %41, %42, %43, %44, %45, %46, %47, "
    "%48, %49, %50, %51, %52, %53, %54, %55, %56, %57, %58, %59, %60, %61, %62, %63}, "
    "{%64, %65, %66, %67}, db, p, 1, 1, %70;\n}\n"
    : "+f"(d[0]), "+f"(d[1]), "+f"(d[2]), "+f"(d[3]), "+f"(d[4]), "+f"(d[5]), "+f"(d[6]), "+f"(d[7]), "+f"(d[8]), "+f"(d[9]), "+f"(d[10]), "+f"(d[11]), "+f"(d[12]), "+f"(d[13]), "+f"(d[14]), "+f"(d[15]), "+f"(d[16]), "+f"(d[17]), "+f"(d[18]), "+f"(d[19]), "+f"(d[20]), "+f"(d[21]), "+f"(d[22]), "+f"(d[23]), "+f"(d[24]), "+f"(d[25]), "+f"(d[26]), "+f"(d[27]), "+f"(d[28]), "+f"(d[29]), "+f"(d[30]), "+f"(d[31]), "+f"(d[32]), "+f"(d[33]), "+f"(d[34]), "+f"(d[35]), "+f"(d[36]), "+f"(d[37]), "+f"(d[38]), "+f"(d[39]), "+f"(d[40]), "+f"(d[41]), "+f"(d[42]), "+f"(d[43]), "+f"(d[44]), "+f"(d[45]), "+f"(d[46]), "+f"(d[47]), "+f"(d[48]), "+f"(d[49]), "+f"(d[50]), "+f"(d[51]), "+f"(d[52]), "+f"(d[53]), "+f"(d[54]), "+f"(d[55]), "+f"(d[56]), "+f"(d[57]), "+f"(d[58]), "+f"(d[59]), "+f"(d[60]), "+f"(d[61]), "+f"(d[62]), "+f"(d[63])
    : "r"(a0), "r"(a1), "r"(a2), "r"(a3), "r"(db), "r"(scale_d), "n"(TB));
}
template<int TB> __device__ __forceinline__ void wgmma_m64n256k16_ss(float (&d)[128], uint32_t da, uint32_t db, int scale_d) {
  asm volatile("{\n.reg .pred p;\n.reg .b64 da, db;\nsetp.ne.b32 p, %130, 0;\nmov.b64 da, {%128, 0x40000040};\nmov.b64 db, {%129, 0x40000040};\n"
    "wgmma.mma_async.sync.aligned.m64n256k16.f32.bf16.bf16 "
    "{%0, %1, %2, %3, %4, %5, %6, %7, %8, %9, %10, %11, %12, %13, %14, %15, "
    "%16, %17, %18, %19, %20, %21, %22, %23, %24, %25, %26, %27, %28, %29, %30, %31, "
    "%32, %33, %34, %35, %36, %37, %38, %39, %40, %41, %42, %43, %44, %45, %46, %47, "
    "%48, %49, %50, %51, %52, %53, %54, %55, %56, %57, %58, %59, %60, %61, %62, %63, "
    "%64, %65, %66, %67, %68, %69, %70, %71, %72, %73, %74, %75, %76, %77, %78, %79, "
    "%80, %81, %82, %83, %84, %85, %86, %87, %88, %89, %90, %91, %92, %93, %94, %95, "
    "%96, %97, %98, %99, %100, %101, %102, %103, %104, %105, %106, %107, %108, %109, %110, %111, "
    "%112, %113, %114, %115, %116, %117, %118, %119, %120, %121, %122, %123, %124, %125, %126, %127}, "
    "da, db, p, 1, 1, 0, %131;\n}\n"
    : "+f"(d[0]), "+f"(d[1]), "+f"(d[2]), "+f"(d[3]), "+f"(d[4]), "+f"(d[5]), "+f"(d[6]), "+f"(d[7]), "+f"(d[8]), "+f"(d[9]), "+f"(d[10]), "+f"(d[11]), "+f"(d[12]), "+f"(d[13]), "+f"(d[14]), "+f"(d[15]), "+f"(d[16]), "+f"(d[17]), "+f"(d[18]), "+f"(d[19]), "+f"(d[20]), "+f"(d[21]), "+f"(d[22]), "+f"(d[23]), "+f"(d[24]), "+f"(d[25]), "+f"(d[26]), "+f"(d[27]), "+f"(d[28]), "+f"(d[29]), "+f"(d[30]), "+f"(d[31]), "+f"(d[32]), "+f"(d[33]), "+f"(d[34]), "+f"(d[35]), "+f"(d[36]), "+f"(d[37]), "+f"(d[38]), "+f"(d[39]), "+f"(d[40]), "+f"(d[41]), "+f"(d[42]), "+f"(d[43]), "+f"(d[44]), "+f"(d[45]), "+f"(d[46]), "+f"(d[47]), "+f"(d[48]), "+f"(d[49]), "+f"(d[50]), "+f"(d[51]), "+f"(d[52]), "+f"(d[53]), "+f"(d[54]), "+f"(d[55]), "+f"(d[56]), "+f"(d[57]), "+f"(d[58]), "+f"(d[59]), "+f"(d[60]), "+f"(d[61]), "+f"(d[62]), "+f"(d[63]), "+f"(d[64]), "+f"(d[65]), "+f"(d[66]), "+f"(d[67]), "+f"(d[68]), "+f"(d[69]), "+f"(d[70]), "+f"(d[71]), "+f"(d[72]), "+f"(d[73]), "+f"(d[74]), "+f"(d[75]), "+f"(d[76]), "+f"(d[77]), "+f"(d[78]), "+f"(d[79]), "+f"(d[80]), "+f"(d[81]), "+f"(d[82]), "+f"(d[83]), "+f"(d[84]), "+f"(d[85]), "+f"(d[86]), "+f"(d[87]), "+f"(d[88]), "+f"(d[89]), "+f"(d[90]), "+f"(d[91]), "+f"(d[92]), "+f"(d[93]), "+f"(d[94]), "+f"(d[95]), "+f"(d[96]), "+f"(d[97]), "+f"(d[98]), "+f"(d[99]), "+f"(d[100]), "+f"(d[101]), "+f"(d[102]), "+f"(d[103]), "+f"(d[104]), "+f"(d[105]), "+f"(d[106]), "+f"(d[107]), "+f"(d[108]), "+f"(d[109]), "+f"(d[110]), "+f"(d[111]), "+f"(d[112]), "+f"(d[113]), "+f"(d[114]), "+f"(d[115]), "+f"(d[116]), "+f"(d[117]), "+f"(d[118]), "+f"(d[119]), "+f"(d[120]), "+f"(d[121]), "+f"(d[122]), "+f"(d[123]), "+f"(d[124]), "+f"(d[125]), "+f"(d[126]), "+f"(d[127])
    : "r"(da), "r"(db), "r"(scale_d), "n"(TB));
}
template<int TB> __device__ __forceinline__ void wgmma_m64n96k16_ss(float (&d)[48], uint32_t da, uint32_t db, int scale_d) {
  asm volatile("{\n.reg .pred p;\n.reg .b64 da, db;\nsetp.ne.b32 p, %50, 0;\nmov.b64 da, {%48, 0x40000040};\nmov.b64 db, {%49, 0x40000040};\n"
    "wgmma.mma_async.sync.aligned.m64n96k16.f32.bf16.bf16 "
    "{%0, %1, %2, %3, %4, %5, %6, %7, %8, %9, %10, %11, %12, %13, %14, %15, "
    "%16, %17, %18, %19, %20, %21, %22, %23, %24, %25, %26, %27, %28, %29, %30, %31, "
    "%32, %33, %34, %35, %36, %37, %38, %39, %40, %41, %42, %43, %44, %45, %46, %47}, "
    "da, db, p, 1, 1, 0, %51;\n}\n"
    : "+f"(d[0]), "+f"(d[1]), "+f"(d[2]), "+f"(d[3]), "+f"(d[4]), "+f"(d[5]), "+f"(d[6]), "+f"(d[7]), "+f"(d[8]), "+f"(d[9]), "+f"(d[10]), "+f"(d[11]), "+f"(d[12]), "+f"(d[13]), "+f"(d[14]), "+f"(d[15]), "+f"(d[16]), "+f"(d[17]), "+f"(d[18]), "+f"(d[19]), "+f"(d[20]), "+f"(d[21]), "+f"(d[22]), "+f"(d[23]), "+f"(d[24]), "+f"(d[25]), "+f"(d[26]), "+f"(d[27]), "+f"(d[28]), "+f"(d[29]), "+f"(d[30]), "+f"(d[31]), "+f"(d[32]), "+f"(d[33]), "+f"(d[34]), "+f"(d[35]), "+f"(d[36]), "+f"(d[37]), "+f"(d[38]), "+f"(d[39]), "+f"(d[40]), "+f"(d[41]), "+f"(d[42]), "+f"(d[43]), "+f"(d[44]), "+f"(d[45]), "+f"(d[46]), "+f"(d[47])
    : "r"(da), "r"(db), "r"(scale_d), "n"(TB));
}
__device__ __align__(1024) __nv_bfloat16 g_xn[SEQ * DM];
__device__ __align__(1024) __nv_bfloat16 g_k[NH * SEQ * HD];
__device__ __align__(1024) __nv_bfloat16 g_v[NH * SEQ * HD];
__device__ __align__(1024) __nv_bfloat16 g_ctx[SEQ * HDALL];
__device__ __align__(1024) __nv_bfloat16 g_h[SEQ * DM];
__device__ __align__(1024) __nv_bfloat16 g_act[SEQ * FF];
__device__ __align__(1024) float g_cs[2 * FF];
__device__ __align__(1024) float2 g_stats[16 * 8 * 128];
__device__ __align__(1024) uint32_t g_sync[320 * 8];
__device__ unsigned long long g_ticket;
constexpr int C_XN = 0, C_CS = 16, C_KV = 32, C_CTX = 160, C_H = 224, C_ACT = 240;

struct Softmax { float m0, m1, mc0, mc1, l0, l1; int th0, th1; };
constexpr float SM_C = 0.08838834764831845f * 1.4426950408889634f;
constexpr float SM_TAU = 16.f;

__device__ __forceinline__ void row_max(const float (&s)[64], float& mx0, float& mx1) {
  float a0[4], a1[4];
#pragma unroll
  for (int i = 0; i < 4; i++) { a0[i] = fmaxf(s[4 * i], s[4 * i + 1]); a1[i] = fmaxf(s[4 * i + 2], s[4 * i + 3]); }
#pragma unroll
  for (int j = 4; j < 16; j++) {
    a0[j & 3] = fmaxf(a0[j & 3], fmaxf(s[4 * j], s[4 * j + 1])); a1[j & 3] = fmaxf(a1[j & 3], fmaxf(s[4 * j + 2], s[4 * j + 3]));
  }
  mx0 = fmaxf(fmaxf(a0[0], a0[1]), fmaxf(a0[2], a0[3])); mx1 = fmaxf(fmaxf(a1[0], a1[1]), fmaxf(a1[2], a1[3]));
  mx0 = fmaxf(mx0, __shfl_xor_sync(0xffffffffu, mx0, 1)); mx1 = fmaxf(mx1, __shfl_xor_sync(0xffffffffu, mx1, 1));
  mx0 = fmaxf(mx0, __shfl_xor_sync(0xffffffffu, mx0, 2)); mx1 = fmaxf(mx1, __shfl_xor_sync(0xffffffffu, mx1, 2));
}
__device__ __forceinline__ void sm_set_ref(Softmax& st, float m0, float m1) {
  st.mc0 = m0 * SM_C; st.mc1 = m1 * SM_C;
  const float t0 = m0 + SM_TAU / SM_C, t1 = m1 + SM_TAU / SM_C;
  st.th0 = t0 >= 0.f ? __float_as_int(t0) : (int)0x80000000;
  st.th1 = t1 >= 0.f ? __float_as_int(t1) : (int)0x80000000;
}
__device__ __forceinline__ void sm_first(float (&s)[64], Softmax& st, int row_in_blk, int q) {
#pragma unroll
  for (int j = 0; j < 16; j++) {
    const int c = 8 * j + 2 * q;
    if (c > row_in_blk) s[4 * j] = -INFINITY;
    if (c + 1 > row_in_blk) s[4 * j + 1] = -INFINITY;
    if (c > row_in_blk + 8) s[4 * j + 2] = -INFINITY;
    if (c + 1 > row_in_blk + 8) s[4 * j + 3] = -INFINITY;
  }
  float mx0, mx1;
  row_max(s, mx0, mx1);
  sm_set_ref(st, mx0, mx1);
  st.m0 = mx0; st.m1 = mx1;
  st.l0 = 0.f; st.l1 = 0.f;
}
__device__ __forceinline__ bool sm_next(float (&s)[64], Softmax& st, float& al0, float& al1) {
  int a[4];
#pragma unroll
  for (int i = 0; i < 4; i++) {
    const int o = (i >> 1) * 32 + (i & 1) * 2;
    a[i] = __vimax3_s32(__float_as_int(s[o]), __float_as_int(s[o + 1]), __float_as_int(s[o + 4]));
  }
#pragma unroll
  for (int i = 0; i < 4; i++) {
    const int o = (i >> 1) * 32 + (i & 1) * 2;
    a[i] = __vimax3_s32(a[i], __float_as_int(s[o + 5]), __float_as_int(s[o + 8]));
#pragma unroll
    for (int k = 2; k < 7; k++) a[i] = __vimax3_s32(a[i], __float_as_int(s[o + 4 * k + 1]), __float_as_int(s[o + 4 * k + 4]));
  }
  const int mx0 = __vimax3_s32(a[0], a[2], max(__float_as_int(s[29]), __float_as_int(s[61])));
  const int mx1 = __vimax3_s32(a[1], a[3], max(__float_as_int(s[31]), __float_as_int(s[63])));
  const bool bad = __any_sync(0xffffffffu, mx0 >= st.th0 || mx1 >= st.th1);
  if (bad) {
    float d0, d1;
    row_max(s, d0, d1);
    d0 = fmaxf(d0, st.m0); d1 = fmaxf(d1, st.m1);
    al0 = ex2((st.m0 - d0) * SM_C); al1 = ex2((st.m1 - d1) * SM_C);
    st.m0 = d0; st.m1 = d1;
    sm_set_ref(st, d0, d1);
    st.l0 *= al0; st.l1 *= al1;
  }
  return bad;
}
template<int J0, int J1>
__device__ __forceinline__ void sm_exp(float (&s)[64], const Softmax& st) {
  const float n0 = -st.mc0, n1 = -st.mc1;
#pragma unroll
  for (int j = J0; j < J1; j++) {
    s[4 * j] = ex2(fmaf(s[4 * j], SM_C, n0)); s[4 * j + 1] = ex2(fmaf(s[4 * j + 1], SM_C, n0));
    s[4 * j + 2] = ex2(fmaf(s[4 * j + 2], SM_C, n1)); s[4 * j + 3] = ex2(fmaf(s[4 * j + 3], SM_C, n1));
  }
}
__device__ __forceinline__ void sm_sum_cvt(const float (&s)[64], uint32_t (&p)[32], Softmax& st) {
  float r0 = 0.f, r1 = 0.f, r2 = 0.f, r3 = 0.f;
#pragma unroll
  for (int j = 0; j < 16; j++) { r0 += s[4 * j]; r1 += s[4 * j + 1]; r2 += s[4 * j + 2]; r3 += s[4 * j + 3]; }
  st.l0 += r0 + r1; st.l1 += r2 + r3;
#pragma unroll
  for (int i = 0; i < 32; i++) p[i] = pack_bf16(s[2 * i], s[2 * i + 1]);
}
__device__ __forceinline__ void issue_qk(float (&s)[64], const uint32_t (&qf)[32], uint32_t ks) {
  const uint32_t db = desc_lo(ks, 16);
#pragma unroll
  for (int kk = 0; kk < 8; kk++)
    wgmma_m64n128k16_rs<0>(s, qf[4 * kk], qf[4 * kk + 1], qf[4 * kk + 2], qf[4 * kk + 3], db + (kk >> 2) * 1024 + (kk & 3) * 2, kk != 0);
}
__device__ __forceinline__ void issue_pv(float (&o)[64], const uint32_t (&p)[32], uint32_t vs, int accumulate) {
  const uint32_t db = desc_lo(vs, 16384);
#pragma unroll
  for (int kk = 0; kk < 8; kk++)
    wgmma_m64n128k16_rs<1>(o, p[4 * kk], p[4 * kk + 1], p[4 * kk + 2], p[4 * kk + 3], db + kk * 128, kk == 0 ? accumulate : 1);
}
template<int K0>
__device__ __forceinline__ void issue128(float (&d)[64], uint32_t slot, int wg, bool first) {
  const uint32_t da = desc_lo(slot + wg * 8192, 16), db = desc_lo(slot + 16384, 8192);
#pragma unroll
  for (int k = K0; k < 4; k++) wgmma_m64n128k16_ss<1>(d, da + k * 2, db + k * 128, !(first && k == K0));
}

struct Maps { CUtensorMap ckv, wk, wv, wq, xn, kst, vst, kld, vld, ctxst, ctxld, wo, h, wg, wu, actst, actld, wd; };
struct Ptrs { const __nv_bfloat16 *x, *wg, *wu, *wo, *wd; __nv_bfloat16* out; };

constexpr uint32_t G_ST = 49152, S_ST = 32768;
constexpr uint32_t O_STG = 196608, O_CS = 229376, O_BAR = 231168;
constexpr uint32_t B_GF = O_BAR, B_GE = O_BAR + 32, B_SF = O_BAR + 64, B_SE = O_BAR + 112, B_TF = O_BAR + 160, B_TE = O_BAR + 176,
                   B_XR = O_BAR + 192, B_XF = O_BAR + 208, B_CS = O_BAR + 224;
constexpr int MK_SMEM = 232448;

__device__ __forceinline__ int attn_qblock(int h, int r, int t) {
  return t == 0 ? 15 - r : (t == 1 ? 8 + r : (((t == 2) == ((h & 1) != 0)) ? r : 7 - r));
}

__global__ void __cluster_dims__(2, 1, 1) __launch_bounds__(384, 1)
k_mega(const __grid_constant__ Maps maps, const __grid_constant__ Ptrs ptrs) {
  extern __shared__ __align__(1024) uint8_t smem_raw[];
  const uint32_t sb = smem_u32(smem_raw);
  const int wg = __shfl_sync(0xffffffffu, threadIdx.x >> 7, 0);
  const int b = blockIdx.x, h = b >> 2, r = b & 3, rho = b & 1;
  const int tm = b >> 3, tn = (b >> 1) & 3;
  if (threadIdx.x == 0) {
    for (int s = 0; s < 4; s++) { mbar_init(sb + B_GF + 8 * s, 1); mbar_init(sb + B_GE + 8 * s, 16); }
    for (int s = 0; s < 6; s++) { mbar_init(sb + B_SF + 8 * s, 1); mbar_init(sb + B_SE + 8 * s, 8); }
    for (int s = 0; s < 2; s++) {
      mbar_init(sb + B_TF + 8 * s, 4); mbar_init(sb + B_TE + 8 * s, 1); mbar_init(sb + B_XR + 8 * s, 1); mbar_init(sb + B_XF + 8 * s, 1);
    }
    mbar_init(sb + B_CS, 1);
    asm volatile("fence.mbarrier_init.release.cluster;" ::: "memory");
  }
  __syncthreads();
  cluster_arrive();
  cluster_wait();

  if (wg == 2) {
    reg_dealloc<40>();
    const int warp = (threadIdx.x >> 5) & 3, lane = threadIdx.x & 31;
    if (warp == 0) {
      if (lane == 0) {
        PROF_G(0, 16);
        const uint32_t ep1 = (uint32_t)(atomicAdd(&g_ticket, 1ULL) >> 7) + 1;
        for (int f = 0; f < 32; f++) {
          const int st = f & 3, kb = f & 7, mb = (3 - (f >> 3)) * 4 + r;
          const uint32_t bar = sb + B_GF + 8 * st, sa = sb + st * G_ST;
          mbar_wait<1>(sb + B_GE + 8 * st, ((f >> 2) & 1) ^ 1);
          mbar_expect_tx(bar, G_ST);
          tma_load_2d(sa, &maps.ckv, bar, kb * 64, mb * 128);
          tma_load_3d_mc(sa + 16384 + rho * 16384, rho ? &maps.wv : &maps.wk, bar, 0, kb * 64, h * 2);
          if (f == 8) {
            prefetch_3d(&maps.wq, 0, r * 128, h * 2); prefetch_3d(&maps.wq, 0, r * 128 + 64, h * 2);
          }
        }
        int sl = 0; uint32_t ph = 1;
        auto s_acq = [&](uint32_t bytes) -> uint32_t {
          mbar_wait<2>(sb + B_SE + 8 * sl, ph);
          mbar_expect_tx(sb + B_SF + 8 * sl, bytes);
          return sb + sl * S_ST;
        };
        auto s_nxt = [&]() { if (++sl == 6) { sl = 0; ph ^= 1; } };
        auto g_drain = [&](int d, uint32_t par) {
          if (d == 0) mbar_wait<3>(sb + B_GE, par);
          if (d == 1) mbar_wait<3>(sb + B_GE + 8, par);
          if (d == 3) mbar_wait<3>(sb + B_GE + 16, par);
          if (d == 4) mbar_wait<3>(sb + B_GE + 24, par);
        };
        for (int t = 0; t < 4; t++) {
          const int qb = attn_qblock(h, r, t);
          flag_wait<4>(&g_sync[(C_XN + qb) * 8], ep1 * 24);
          if (t == 0) PROF_T(1, 3);
          for (int kb = 0; kb < 8; kb++) {
            if (t == 0) g_drain(kb, 1);
            const uint32_t d = s_acq(S_ST), bar = sb + B_SF + 8 * sl;
            tma_load_2d(d, &maps.xn, bar, kb * 64, qb * 128);
            tma_load_3d(d + 16384, &maps.wq, bar, 0, kb * 64, h * 2);
            s_nxt();
          }
          auto ld_kv = [&](const CUtensorMap* mp, int blk) {
            const uint32_t d = s_acq(S_ST);
            tma_load_3d(d, mp, sb + B_SF + 8 * sl, 0, h * SEQ + blk * 128, 0);
            s_nxt();
          };
          if (t == 0) PROF_T(1, 4);
          if (t == 0) flag_wait_relaxed<5>(&g_sync[(C_KV + h * 4) * 8], ep1 * 8);
          if (t == 0) PROF_T(1, 5);
          ld_kv(&maps.kld, qb);
          for (int j = qb; j > 0; j--) {
            if (t == 0 && (j & 3) == 0) flag_wait_relaxed<5>(&g_sync[(C_KV + h * 4 + 4 - (j >> 2)) * 8], ep1 * 8);
            ld_kv(&maps.kld, j - 1);
            ld_kv(&maps.vld, j);
          }
          ld_kv(&maps.vld, 0);
          if (t == 2) { prefetch_l2(ptrs.wo + b * 32 * DM, 32 * DM * 2); prefetch_l2(ptrs.x + b * 16 * DM, 16 * DM * 2); }
        }
        const int fg = tn * 2 + rho;
        flag_wait<6>(&g_sync[C_CS * 8], ep1 * 128);
        mbar_expect_tx(sb + B_CS, 1792);
        bulk_load(sb + O_CS, g_cs + fg * 224, 896, sb + B_CS);
        bulk_load(sb + O_CS + 896, g_cs + FF + fg * 224, 896, sb + B_CS);
        prefetch_l2(ptrs.wd + b * 14 * DM, 14 * DM * 2);
        {
          const int c1 = tm < 4 ? 1 : 0;
          for (int kb = 0; kb < 32; kb++) {
            const int cls = (kb >> 4) ^ c1;
            if ((kb & 15) == 0) { PROF_T(1, 6 + (kb >> 4) * 2); flag_wait_relaxed<7>(&g_sync[(C_CTX + (tm * 2 + rho) * 2 + cls) * 8], ep1 * 16); PROF_T(1, 7 + (kb >> 4) * 2); }
            const int k0 = (16 * rho + ((kb >> 1) & 7) * 2 + cls) * 128 + (kb & 1) * 64;
            const uint32_t d = s_acq(S_ST), bar = sb + B_SF + 8 * sl;
            tma_load_2d(d, &maps.ctxld, bar, k0, tm * 128);
            tma_load_3d(d + 16384, &maps.wo, bar, 0, k0, tn * 2);
            s_nxt();
          }
        }
        PROF_T(1, 0);
        for (int f = 0; f < 16; f++) {
          const int st = f & 3, kb = f & 7, x0 = fg * 224 + (f >> 3) * 128;
          const uint32_t bar = sb + B_GF + 8 * st, sa = sb + st * G_ST;
          mbar_wait<8>(sb + B_GE + 8 * st, (f >> 2) & 1);
          mbar_expect_only(bar, 32768);
          tma_load_2d(sa + 16384, &maps.wg, bar, x0, kb * 64);
          tma_load_2d(sa + 24576, &maps.wg, bar, x0 + 64, kb * 64);
          tma_load_2d(sa + 32768, &maps.wu, bar, x0, kb * 64);
          tma_load_2d(sa + 40960, &maps.wu, bar, x0 + 64, kb * 64);
          if (f >= 3) {
            if (f == 3) {
              PROF_T(1, 10);
              flag_wait_relaxed<9>(&g_sync[(C_H + tm) * 8], ep1 * 16);
              PROF_T(1, 11);
              for (int i = 0; i < 3; i++) {
                mbar_expect_tx(sb + B_GF + 8 * i, 16384);
                tma_load_2d_mc(sb + i * G_ST + rho * 8192, &maps.h, sb + B_GF + 8 * i, i * 64, tm * 128 + rho * 64);
              }
            }
            mbar_expect_tx(bar, 16384);
            tma_load_2d_mc(sa + rho * 8192, &maps.h, bar, kb * 64, tm * 128 + rho * 64);
          }
        }
        PROF_T(1, 1);
        for (int d = 0; d < 16; d++) {
          if (d < 6) g_drain(d, 0);
          if ((d & 7) == 0) { PROF_T(1, 12 + (d >> 3) * 2); flag_wait_relaxed<10>(&g_sync[(C_ACT + (tm * 2 + rho) * 2 + (d >> 3)) * 8], ep1 * 8); PROF_T(1, 13 + (d >> 3) * 2); }
          const int k0 = (4 * rho + ((d >> 1) & 3)) * 224 + (d < 8 ? (d & 1) * 64 : 128 + (d & 1) * 32);
          const uint32_t dd = s_acq(S_ST), bar = sb + B_SF + 8 * sl;
          tma_load_2d(dd, &maps.actld, bar, k0, tm * 128);
          tma_load_3d(dd + 16384, &maps.wd, bar, 0, k0, tn * 2);
          s_nxt();
        }
        PROF_T(1, 2);
      }
    } else {
      for (int i = warp - 1; i < 16; i += 3) {
        const int row = b * 16 + i;
        const uint4* src = reinterpret_cast<const uint4*>(ptrs.x + row * DM);
        const uint4 a = __ldg(src + lane), c = __ldg(src + lane + 32);
        uint32_t w[8] = {a.x, a.y, a.z, a.w, c.x, c.y, c.z, c.w};
        float s = 0.f;
#pragma unroll
        for (int k = 0; k < 8; k++) s += bf16lo(w[k]) + bf16hi(w[k]);
#pragma unroll
        for (int o = 16; o > 0; o >>= 1) s += __shfl_xor_sync(0xffffffffu, s, o);
        const float mean = s * (1.f / 512.f);
        float ss = 0.f;
#pragma unroll
        for (int k = 0; k < 8; k++) { const float u = bf16lo(w[k]) - mean, v = bf16hi(w[k]) - mean; ss += u * u + v * v; }
#pragma unroll
        for (int o = 16; o > 0; o >>= 1) ss += __shfl_xor_sync(0xffffffffu, ss, o);
        const float rstd = rsqrtf(ss * (1.f / 512.f) + 1e-5f);
#pragma unroll
        for (int k = 0; k < 8; k++) w[k] = pack_bf16((bf16lo(w[k]) - mean) * rstd, (bf16hi(w[k]) - mean) * rstd);
        uint4* dst = reinterpret_cast<uint4*>(g_xn + row * DM);
        dst[lane] = make_uint4(w[0], w[1], w[2], w[3]);
        dst[lane + 32] = make_uint4(w[4], w[5], w[6], w[7]);
      }
      __syncwarp();
      if (lane == 0) flag_arrive(&g_sync[(C_XN + (b >> 3)) * 8]);
      if (warp == 3) {
        if (lane < 28) {
          const int cp = lane % 14, hf = lane / 14;
          const uint32_t* src = reinterpret_cast<const uint32_t*>((b < 64 ? ptrs.wg : ptrs.wu) + (size_t)hf * 256 * FF + (b & 63) * 28 + cp * 2);
          float s0 = 0.f, s1 = 0.f;
#pragma unroll 8
          for (int k = 0; k < 256; k++) { const uint32_t v = __ldg(src + k * (FF / 2)); s0 += bf16lo(v); s1 += bf16hi(v); }
          const float t0 = __shfl_down_sync(0x0fffffffu, s0, 14), t1 = __shfl_down_sync(0x0fffffffu, s1, 14);
          if (lane < 14) *reinterpret_cast<float2*>(g_cs + b * 28 + cp * 2) = make_float2(s0 + t0, s1 + t1);
        }
        __syncwarp();
        if (lane == 0) flag_arrive(&g_sync[C_CS * 8]);
      } else if (lane == 0) {
        const int w = warp - 1;
        const uint32_t stg = sb + O_STG + w * 16384;
        const uint32_t xr_peer = mapa(sb + B_XR + 8 * w, rho ^ 1);
        for (int job = 0; job < 15; job++) {
          mbar_wait<11>(sb + B_TF + 8 * w, job & 1);
          if (w == 0) PROF_T(3, job);
          uint32_t* flag = nullptr;
          if (job < 8) {
            const int i = job >> 1;
            tma_store_3d((job & 1) ? &maps.vst : &maps.kst, stg, 0, h * SEQ + ((3 - i) * 4 + r) * 128 + w * 64, 0);
            if (job & 1) flag = &g_sync[(C_KV + h * 4 + i) * 8];
          } else if (job < 12) {
            const int qb = attn_qblock(h, r, job - 8);
            tma_store_3d(&maps.ctxst, stg, 0, qb * 128 + w * 64, h * 2);
            flag = &g_sync[(C_CTX + (qb * 2 + (h >> 4)) * 2 + (h & 1)) * 8];
          } else if (job == 12) {
            tma_store_2d(&maps.h, stg, tn * 128 + rho * 64, tm * 128 + w * 64);
            bulk_store(g_stats + (tm * 8 + tn * 2 + rho) * 128 + w * 64, stg + 8192, 512);
            flag = &g_sync[(C_H + tm) * 8];
          } else {
            const int x0 = (tn * 2 + rho) * 224 + (job - 13) * 128;
            tma_store_2d(&maps.actst, stg, x0, tm * 128 + w * 64);
            tma_store_2d(&maps.actst, stg + 8192, x0 + (job == 13 ? 64 : 32), tm * 128 + w * 64);
            flag = &g_sync[(C_ACT + (tm * 2 + (tn >> 1)) * 2 + (job - 13)) * 8];
          }
          bulk_commit();
          bulk_wait_read();
          if (w == 0) PROF_T(4, job);
          mbar_arrive(sb + B_TE + 8 * w);
          if (job == 11 || job == 14) mbar_arrive_cl(xr_peer);
          if (flag) { bulk_wait_all(); if (w == 0) PROF_T(5, job); flag_arrive_relaxed(flag); }
          if (w == 0) PROF_T(2, job);
        }
      }
    }
    __syncwarp();
    cluster_arrive();
    cluster_wait();
  } else {
    reg_alloc<232>();
    const int lane = threadIdx.x & 31, warp = (threadIdx.x >> 5) & 3, q = lane & 3;
    const int row_in_blk = wg * 64 + warp * 16 + (lane >> 2);
    const uint32_t stg = sb + O_STG + wg * 16384;
    const uint32_t stm = stg + (warp * 16 + (lane & 7) + ((lane >> 3) & 1) * 8) * 128 + (((lane >> 4) ^ (lane & 7)) << 4);
    const uint32_t ge_cl = mapa(sb + B_GE, (lane & 1) ^ rho);
    auto g_release = [&](int st) { if (lane < 2) mbar_arrive_cl(ge_cl + 8 * st); };
    uint32_t jpar = 1;
    auto stg_acquire = [&]() { mbar_wait<20>(sb + B_TE + 8 * wg, jpar); jpar ^= 1; };
    auto stg_publish = [&]() { fence_async_smem(); __syncwarp(); if (lane == 0) mbar_arrive(sb + B_TF + 8 * wg); };
    auto stg_put = [&](int atom, int jp, uint32_t a, uint32_t c, uint32_t d, uint32_t e) {
      stmatrix_x4((stm + atom * 8192) ^ (((2 * jp) & 7) << 4), a, c, d, e);
    };
    if (threadIdx.x == 0) PROF_T(0, 0);

    int sl = 0; uint32_t ph = 0;
    auto s_nxt = [&]() { if (++sl == 6) { sl = 0; ph ^= 1; } };
    auto s_release = [&](int a) { if (lane == 0) mbar_arrive(sb + B_SE + 8 * a); };
    float s[64];
    uint32_t qf[32];
    {
      float acc[128];
      uint32_t pk[64];
      auto put_tile = [&](int half) {
        stg_acquire();
#pragma unroll
        for (int jp = 0; jp < 8; jp++)
          stg_put(jp >> 2, jp, pk[half * 32 + 4 * jp], pk[half * 32 + 4 * jp + 1], pk[half * 32 + 4 * jp + 2], pk[half * 32 + 4 * jp + 3]);
        stg_publish();
      };
#pragma unroll
      for (int i = 0; i < 64; i++) pk[i] = 0;
      for (int i = 0; i < 4; i++) {
#pragma unroll
        for (int kb = 0; kb < 8; kb++) {
          const int st = kb & 3;
          mbar_wait<21>(sb + B_GF + 8 * st, (kb >> 2) & 1);
          const uint32_t da = desc_lo(sb + st * G_ST + wg * 8192, 16), db = desc_lo(sb + st * G_ST + 16384, 8192);
          wgmma_fence();
#pragma unroll
          for (int k = 0; k < 4; k++) wgmma_m64n256k16_ss<1>(acc, da + k * 2, db + k * 128, (kb | k) != 0);
          wgmma_commit();
          if (kb > 0) { wgmma_wait<1>(); g_release((kb - 1) & 3); }
          if (kb == 0 && i > 0) put_tile(0);
          if (kb == 4 && i > 0) put_tile(1);
        }
        wgmma_wait<0>();
        g_release(3);
        fence_regs(acc);
#pragma unroll
        for (int k = 0; k < 64; k++) pk[k] = pack_bf16(acc[2 * k], acc[2 * k + 1]);
        if (threadIdx.x == 0) PROF_T(0, 1 + i);
      }
      int prev = 0;
#pragma unroll
      for (int kb = 0; kb < 8; kb++) {
        mbar_wait<22>(sb + B_SF + 8 * sl, ph);
        wgmma_fence();
        issue128<0>(s, sb + sl * S_ST, wg, kb == 0);
        wgmma_commit();
        if (kb > 0) { wgmma_wait<1>(); s_release(prev); }
        prev = sl; s_nxt();
        if (kb == 0) put_tile(0);
        if (kb == 4) put_tile(1);
      }
      wgmma_wait<0>();
      fence_regs(s);
      s_release(prev);
#pragma unroll
      for (int k = 0; k < 32; k++) qf[k] = pack_bf16(s[2 * k], s[2 * k + 1]);
    }
    if (threadIdx.x == 0) PROF_T(0, 5);
    {
      float o[64]; uint32_t p[32];
      Softmax st; float al0 = 1.f, al1 = 1.f;
#pragma unroll
      for (int i = 0; i < 64; i++) o[i] = 0.f;
      if (wg == 1) named_bar_arrive(1, 256);
      for (int t = 0; t < 4; t++) {
        const int qb = attn_qblock(h, r, t);
        if (threadIdx.x == 0) PROF_T(6, t);
        mbar_wait<23>(sb + B_SF + 8 * sl, ph);
        if (threadIdx.x == 0) PROF_T(6, 4 + t);
        named_bar_sync(1 + wg, 256);
        wgmma_fence();
        issue_qk(s, qf, sb + sl * S_ST);
        wgmma_commit();
        named_bar_arrive(2 - wg, 256);
        wgmma_wait<0>(); fence_regs(s);
        s_release(sl); s_nxt();
        sm_first(s, st, row_in_blk, q);
        sm_exp<0, 16>(s, st);
        sm_sum_cvt(s, p, st);
        mbar_wait<24>(sb + B_SF + 8 * sl, ph);
        if (threadIdx.x == 0) PROF_T(6, 8 + t);
        for (int j = qb; j > 0; j--) {
          const int ks = sl; s_nxt();
          const int vs = sl;
          named_bar_sync(1 + wg, 256);
          wgmma_fence();
          issue_qk(s, qf, sb + ks * S_ST);
          wgmma_commit();
          mbar_wait<25>(sb + B_SF + 8 * vs, ph);
          s_nxt();
          wgmma_fence();
          issue_pv(o, p, sb + vs * S_ST, j != qb);
          wgmma_commit();
          named_bar_arrive(2 - wg, 256);
          wgmma_wait<1>(); fence_regs(s);
          s_release(ks);
          const bool bad = sm_next(s, st, al0, al1);
          sm_exp<0, 4>(s, st);
          fence_regs(s);
          mbar_wait<26>(sb + B_SF + 8 * sl, ph);
          wgmma_wait<0>(); fence_regs(o); fence_regs(p);
          s_release(vs);
          if (bad) {
#pragma unroll
            for (int i = 0; i < 16; i++) { o[4 * i] *= al0; o[4 * i + 1] *= al0; o[4 * i + 2] *= al1; o[4 * i + 3] *= al1; }
          }
          sm_exp<4, 16>(s, st);
          sm_sum_cvt(s, p, st);
        }
        if (threadIdx.x == 0) PROF_T(0, 6 + t);
        const int vs = sl; s_nxt();
        named_bar_sync(1 + wg, 256);
        wgmma_fence();
        issue_pv(o, p, sb + vs * S_ST, qb != 0);
        wgmma_commit();
        if (t < 3 || wg == 0) named_bar_arrive(2 - wg, 256);
        float l0 = st.l0, l1 = st.l1;
        const int nkb = t < 3 ? 8 : 32;
        mbar_wait<27>(sb + B_SF + 8 * sl, ph);
        wgmma_fence();
        issue128<0>(s, sb + sl * S_ST, wg, true);
        wgmma_commit();
        int prev = sl; s_nxt();
        l0 += __shfl_xor_sync(0xffffffffu, l0, 1); l1 += __shfl_xor_sync(0xffffffffu, l1, 1);
        l0 += __shfl_xor_sync(0xffffffffu, l0, 2); l1 += __shfl_xor_sync(0xffffffffu, l1, 2);
        const float i0 = 1.f / l0, i1 = 1.f / l1;
        wgmma_wait<1>(); fence_regs(o); fence_regs(p);
        s_release(vs);
        auto put_ctx = [&](int jp) {
          stg_put(jp >> 2, jp, pack_bf16(o[8 * jp] * i0, o[8 * jp + 1] * i0), pack_bf16(o[8 * jp + 2] * i1, o[8 * jp + 3] * i1),
                  pack_bf16(o[8 * jp + 4] * i0, o[8 * jp + 5] * i0), pack_bf16(o[8 * jp + 6] * i1, o[8 * jp + 7] * i1));
        };
        stg_acquire();
        put_ctx(0); put_ctx(1);
        mbar_wait<28>(sb + B_SF + 8 * sl, ph);
        wgmma_fence();
        issue128<0>(s, sb + sl * S_ST, wg, false);
        wgmma_commit();
        put_ctx(2); put_ctx(3); put_ctx(4);
        wgmma_wait<1>(); s_release(prev); prev = sl; s_nxt();
        mbar_wait<28>(sb + B_SF + 8 * sl, ph);
        wgmma_fence();
        issue128<0>(s, sb + sl * S_ST, wg, false);
        wgmma_commit();
        put_ctx(5); put_ctx(6); put_ctx(7);
        stg_publish();
        wgmma_wait<1>(); s_release(prev); prev = sl; s_nxt();
        for (int kb = 3; kb < nkb; kb++) {
          mbar_wait<29>(sb + B_SF + 8 * sl, ph);
          wgmma_fence();
          issue128<0>(s, sb + sl * S_ST, wg, false);
          wgmma_commit();
          wgmma_wait<1>(); s_release(prev); prev = sl; s_nxt();
        }
        wgmma_wait<0>();
        fence_regs(s);
        s_release(prev);
#pragma unroll
        for (int k = 0; k < 32; k++) qf[k] = pack_bf16(s[2 * k], s[2 * k + 1]);
      }
    }
    if (threadIdx.x == 0) PROF_T(0, 10);
#pragma unroll
    for (int st = 0; st < 4; st++) g_release(st);
    uint32_t xr[16];
    {
      const uint32_t* xs = reinterpret_cast<const uint32_t*>(ptrs.x + (tm * 128 + row_in_blk) * DM + tn * 128 + rho * 64 + 2 * q);
#pragma unroll
      for (int j = 0; j < 8; j++) { xr[2 * j] = __ldg(xs + 4 * j); xr[2 * j + 1] = __ldg(xs + 8 * (DM / 2) + 4 * j); }
    }

    const uint32_t xbuf = stg + (threadIdx.x & 127) * 16;
    const uint32_t xbuf_peer = mapa(xbuf, rho ^ 1), xf_peer = mapa(sb + B_XF + 8 * wg, rho ^ 1);
    auto exchange = [&](float (&d)[64], float (&v)[32], uint32_t par) {
      if ((threadIdx.x & 127) == 0) mbar_expect_tx(sb + B_XF + 8 * wg, 16384);
      mbar_wait_cl<30>(sb + B_XR + 8 * wg, par);
#pragma unroll
      for (int i = 0; i < 8; i++)
        st_async_v4(xbuf_peer + i * 2048, rho ? d[4 * i] : d[32 + 4 * i], rho ? d[4 * i + 1] : d[33 + 4 * i],
                    rho ? d[4 * i + 2] : d[34 + 4 * i], rho ? d[4 * i + 3] : d[35 + 4 * i], xf_peer);
#pragma unroll
      for (int i = 0; i < 32; i++) v[i] = rho ? d[32 + i] : d[i];
    };
    auto exchange_finish = [&](float (&v)[32], uint32_t par) {
      mbar_wait_cl<31>(sb + B_XF + 8 * wg, par);
#pragma unroll
      for (int i = 0; i < 8; i++) {
        const float4 u = lds_v4(xbuf + i * 2048);
        v[4 * i] += u.x; v[4 * i + 1] += u.y; v[4 * i + 2] += u.z; v[4 * i + 3] += u.w;
      }
    };
    {
      float v[32];
      exchange(s, v, 0);
      stg_acquire();
      exchange_finish(v, 0);
      uint32_t hp[16];
      float s0 = 0.f, s1 = 0.f;
#pragma unroll
      for (int j = 0; j < 8; j++) {
        hp[2 * j] = pack_bf16(bf16lo(xr[2 * j]) + v[4 * j], bf16hi(xr[2 * j]) + v[4 * j + 1]);
        hp[2 * j + 1] = pack_bf16(bf16lo(xr[2 * j + 1]) + v[4 * j + 2], bf16hi(xr[2 * j + 1]) + v[4 * j + 3]);
        s0 += bf16lo(hp[2 * j]) + bf16hi(hp[2 * j]); s1 += bf16lo(hp[2 * j + 1]) + bf16hi(hp[2 * j + 1]);
      }
      named_bar_sync(3 + wg, 128);
#pragma unroll
      for (int jp = 0; jp < 4; jp++) stg_put(0, jp, hp[4 * jp], hp[4 * jp + 1], hp[4 * jp + 2], hp[4 * jp + 3]);
      s0 += __shfl_xor_sync(0xffffffffu, s0, 1); s1 += __shfl_xor_sync(0xffffffffu, s1, 1);
      s0 += __shfl_xor_sync(0xffffffffu, s0, 2); s1 += __shfl_xor_sync(0xffffffffu, s1, 2);
      s0 *= (1.f / 64.f); s1 *= (1.f / 64.f);
      float m0 = 0.f, m1 = 0.f;
#pragma unroll
      for (int j = 0; j < 8; j++) {
        const float a = bf16lo(hp[2 * j]) - s0, c = bf16hi(hp[2 * j]) - s0, d = bf16lo(hp[2 * j + 1]) - s1, e = bf16hi(hp[2 * j + 1]) - s1;
        m0 += a * a + c * c; m1 += d * d + e * e;
      }
      m0 += __shfl_xor_sync(0xffffffffu, m0, 1); m1 += __shfl_xor_sync(0xffffffffu, m1, 1);
      m0 += __shfl_xor_sync(0xffffffffu, m0, 2); m1 += __shfl_xor_sync(0xffffffffu, m1, 2);
      if (q == 0) {
        const uint32_t a = stg + 8192 + (warp * 16 + (lane >> 2)) * 8;
        sts_v2(a, s0, m0); sts_v2(a + 64, s1, m1);
      }
      stg_publish();
    }
    if (threadIdx.x == 0) PROF_T(0, 11);
    {
      float mu0, mu1, rs0, rs1;
      uint32_t pg[32], pu[32];
      const uint32_t csb = sb + O_CS + q * 8;
      {
        float acc[128];
#pragma unroll
        for (int kb = 0; kb < 8; kb++) {
          const int st = kb & 3;
          mbar_wait<32>(sb + B_GF + 8 * st, (kb >> 2) & 1);
          const uint32_t da = desc_lo(sb + st * G_ST + wg * 8192, 16), db = desc_lo(sb + st * G_ST + 16384, 8192);
          wgmma_fence();
#pragma unroll
          for (int k = 0; k < 4; k++) wgmma_m64n256k16_ss<1>(acc, da + k * 2, db + k * 128, (kb | k) != 0);
          wgmma_commit();
          if (kb > 0) { wgmma_wait<1>(); g_release((kb - 1) & 3); }
          if (kb == 0) {
            const float2* sp = g_stats + (tm * 8 + 2 * q) * 128 + row_in_blk;
            const float2 a0 = __ldcg(sp), a1 = __ldcg(sp + 128), c0 = __ldcg(sp + 8), c1 = __ldcg(sp + 136);
            float t0 = a0.x + a1.x, t1 = c0.x + c1.x;
            t0 += __shfl_xor_sync(0xffffffffu, t0, 1); t1 += __shfl_xor_sync(0xffffffffu, t1, 1);
            t0 += __shfl_xor_sync(0xffffffffu, t0, 2); t1 += __shfl_xor_sync(0xffffffffu, t1, 2);
            mu0 = t0 * 0.125f; mu1 = t1 * 0.125f;
            float v0 = a0.y + a1.y + 64.f * ((a0.x - mu0) * (a0.x - mu0) + (a1.x - mu0) * (a1.x - mu0));
            float v1 = c0.y + c1.y + 64.f * ((c0.x - mu1) * (c0.x - mu1) + (c1.x - mu1) * (c1.x - mu1));
            v0 += __shfl_xor_sync(0xffffffffu, v0, 1); v1 += __shfl_xor_sync(0xffffffffu, v1, 1);
            v0 += __shfl_xor_sync(0xffffffffu, v0, 2); v1 += __shfl_xor_sync(0xffffffffu, v1, 2);
            rs0 = rsqrtf(v0 * (1.f / 512.f) + 1e-5f); rs1 = rsqrtf(v1 * (1.f / 512.f) + 1e-5f);
          }
        }
        wgmma_wait<0>();
        g_release(3);
        fence_regs(acc);
        mbar_wait<33>(sb + B_CS, 0);
#pragma unroll
        for (int j = 0; j < 16; j++) {
          const float2 cg = lds_v2(csb + j * 32), cu = lds_v2(csb + 896 + j * 32);
          pg[2 * j] = pack_bf16(rs0 * fmaf(-mu0, cg.x, acc[4 * j]), rs0 * fmaf(-mu0, cg.y, acc[4 * j + 1]));
          pg[2 * j + 1] = pack_bf16(rs1 * fmaf(-mu1, cg.x, acc[4 * j + 2]), rs1 * fmaf(-mu1, cg.y, acc[4 * j + 3]));
          pu[2 * j] = pack_bf16(rs0 * fmaf(-mu0, cu.x, acc[64 + 4 * j]), rs0 * fmaf(-mu0, cu.y, acc[64 + 4 * j + 1]));
          pu[2 * j + 1] = pack_bf16(rs1 * fmaf(-mu1, cu.x, acc[64 + 4 * j + 2]), rs1 * fmaf(-mu1, cu.y, acc[64 + 4 * j + 3]));
        }
      }
      if (threadIdx.x == 0) PROF_T(0, 12);
      auto glu = [&](uint32_t g, uint32_t u) -> uint32_t {
        const float a = __fdividef(bf16lo(u), 1.f + ex2(-1.4426950408889634f * bf16lo(g)));
        const float c = __fdividef(bf16hi(u), 1.f + ex2(-1.4426950408889634f * bf16hi(g)));
        return pack_bf16(a, c);
      };
      uint32_t rg[24], ru[24];
      {
        float ag[48], au[48];
#pragma unroll
        for (int kb = 0; kb < 8; kb++) {
          const int st = kb & 3;
          mbar_wait<34>(sb + B_GF + 8 * st, (kb >> 2) & 1);
          const uint32_t da = desc_lo(sb + st * G_ST + wg * 8192, 16), db = desc_lo(sb + st * G_ST + 16384, 8192);
          wgmma_fence();
#pragma unroll
          for (int k = 0; k < 4; k++) {
            wgmma_m64n96k16_ss<1>(ag, da + k * 2, db + k * 128, (kb | k) != 0);
            wgmma_m64n96k16_ss<1>(au, da + k * 2, db + 1024 + k * 128, (kb | k) != 0);
          }
          wgmma_commit();
          if (kb == 0) stg_acquire();
          if (kb < 4) {
#pragma unroll
            for (int jp = 2 * kb; jp < 2 * kb + 2; jp++)
              stg_put(jp >> 2, jp, glu(pg[4 * jp], pu[4 * jp]), glu(pg[4 * jp + 1], pu[4 * jp + 1]),
                      glu(pg[4 * jp + 2], pu[4 * jp + 2]), glu(pg[4 * jp + 3], pu[4 * jp + 3]));
          }
          if (kb == 3) stg_publish();
          if (kb > 0) { wgmma_wait<1>(); g_release((kb - 1) & 3); }
        }
        wgmma_wait<0>();
        g_release(3);
        fence_regs(ag); fence_regs(au);
        if (lane == 0) PROF_T(7, wg * 4 + warp);
#pragma unroll
        for (int j = 0; j < 12; j++) {
          const float2 cg = lds_v2(csb + 512 + j * 32), cu = lds_v2(csb + 896 + 512 + j * 32);
          rg[2 * j] = pack_bf16(rs0 * fmaf(-mu0, cg.x, ag[4 * j]), rs0 * fmaf(-mu0, cg.y, ag[4 * j + 1]));
          rg[2 * j + 1] = pack_bf16(rs1 * fmaf(-mu1, cg.x, ag[4 * j + 2]), rs1 * fmaf(-mu1, cg.y, ag[4 * j + 3]));
          ru[2 * j] = pack_bf16(rs0 * fmaf(-mu0, cu.x, au[4 * j]), rs0 * fmaf(-mu0, cu.y, au[4 * j + 1]));
          ru[2 * j + 1] = pack_bf16(rs1 * fmaf(-mu1, cu.x, au[4 * j + 2]), rs1 * fmaf(-mu1, cu.y, au[4 * j + 3]));
        }
      }
      if (threadIdx.x == 0) PROF_T(0, 13);
      fence_regs(rg); fence_regs(ru);
      if (lane == 0) PROF_T(7, 8 + wg * 4 + warp);
      stg_acquire();
#pragma unroll
      for (int jp = 0; jp < 6; jp++) {
        const uint32_t a = glu(rg[4 * jp], ru[4 * jp]), c = glu(rg[4 * jp + 1], ru[4 * jp + 1]);
        const uint32_t d = glu(rg[4 * jp + 2], ru[4 * jp + 2]), e = glu(rg[4 * jp + 3], ru[4 * jp + 3]);
        if (jp < 4) stg_put(0, jp, a, c, d, e);
        if (jp >= 2) stg_put(1, jp - 2, a, c, d, e);
      }
      stg_publish();
      if (lane == 0) PROF_T(7, 16 + wg * 4 + warp);
      uint32_t hr[16];
      mbar_wait<35>(sb + B_SF + 8 * sl, ph);
      wgmma_fence();
      issue128<0>(s, sb + sl * S_ST, wg, true);
      wgmma_commit();
      int prev = sl; s_nxt();
#pragma unroll 1
      for (int kb = 1; kb < 8; kb++) {
        mbar_wait<35>(sb + B_SF + 8 * sl, ph);
        wgmma_fence();
        issue128<0>(s, sb + sl * S_ST, wg, false);
        wgmma_commit();
        wgmma_wait<1>(); s_release(prev);
        prev = sl; s_nxt();
      }
      {
        const uint32_t* hs = reinterpret_cast<const uint32_t*>(g_h + (tm * 128 + row_in_blk) * DM + tn * 128 + rho * 64 + 2 * q);
#pragma unroll
        for (int j = 0; j < 8; j++) { hr[2 * j] = __ldcg(hs + 4 * j); hr[2 * j + 1] = __ldcg(hs + 8 * (DM / 2) + 4 * j); }
      }
#pragma unroll 1
      for (int g = 0; g < 4; g++) {
        mbar_wait<36>(sb + B_SF + 8 * sl, ph);
        wgmma_fence();
        issue128<0>(s, sb + sl * S_ST, wg, false);
        wgmma_commit();
        wgmma_wait<1>(); s_release(prev); prev = sl; s_nxt();
        mbar_wait<37>(sb + B_SF + 8 * sl, ph);
        wgmma_fence();
        issue128<2>(s, sb + sl * S_ST, wg, false);
        wgmma_commit();
        wgmma_wait<1>(); s_release(prev); prev = sl; s_nxt();
      }
      wgmma_wait<0>();
      fence_regs(s);
      s_release(prev);
      if (threadIdx.x == 0) PROF_T(0, 14);
      float v[32];
      exchange(s, v, 1);
      exchange_finish(v, 1);
      uint32_t* dst = reinterpret_cast<uint32_t*>(ptrs.out + (tm * 128 + row_in_blk) * DM + tn * 128 + rho * 64 + 2 * q);
#pragma unroll
      for (int j = 0; j < 8; j++) {
        dst[4 * j] = pack_bf16(bf16lo(hr[2 * j]) + v[4 * j], bf16hi(hr[2 * j]) + v[4 * j + 1]);
        dst[8 * (DM / 2) + 4 * j] = pack_bf16(bf16lo(hr[2 * j + 1]) + v[4 * j + 2], bf16hi(hr[2 * j + 1]) + v[4 * j + 3]);
      }
    }
    if (threadIdx.x == 0) { PROF_T(0, 15); PROF_G(0, 17); }
    cluster_arrive();
    cluster_wait();
  }
}

typedef CUresult (*PFN_encodeTiled_t)(CUtensorMap*, CUtensorMapDataType, cuuint32_t, void*, const cuuint64_t*, const cuuint64_t*,
                                      const cuuint32_t*, const cuuint32_t*, CUtensorMapInterleave, CUtensorMapSwizzle,
                                      CUtensorMapL2promotion, CUtensorMapFloatOOBfill);
static PFN_encodeTiled_t g_encode = nullptr;
static void make_map(CUtensorMap* m, const void* base, int rank, const cuuint64_t* dims, const cuuint64_t* strides, const cuuint32_t* box) {
  cuuint32_t es[5] = {1, 1, 1, 1, 1};
  g_encode(m, CU_TENSOR_MAP_DATA_TYPE_BFLOAT16, rank, const_cast<void*>(base), dims, strides, box, es, CU_TENSOR_MAP_INTERLEAVE_NONE,
           CU_TENSOR_MAP_SWIZZLE_128B, CU_TENSOR_MAP_L2_PROMOTION_L2_256B, CU_TENSOR_MAP_FLOAT_OOB_FILL_NONE);
}
static void map_2d(CUtensorMap* m, const void* base, int rows, int cols, int brows) {
  cuuint64_t d[2] = {(cuuint64_t)cols, (cuuint64_t)rows}, s[1] = {(cuuint64_t)cols * 2}; cuuint32_t b[2] = {64, (cuuint32_t)brows};
  make_map(m, base, 2, d, s, b);
}
static void map_3d(CUtensorMap* m, const void* base, int rows, int cols, int brows) {
  cuuint64_t d[3] = {64, (cuuint64_t)rows, (cuuint64_t)(cols / 64)}, s[2] = {(cuuint64_t)cols * 2, 128}; cuuint32_t b[3] = {64, (cuuint32_t)brows, 2};
  make_map(m, base, 3, d, s, b);
}

static Maps g_maps;
static Ptrs g_ptrs;
static bool g_init = false;
static void* g_last_in[10];

extern "C" void kernel_launch(void* const* d_in, const int* in_sizes, int n_in, void* d_out, int out_size) {
  bool same = g_init;
  for (int i = 0; i < 10; i++) same = same && g_last_in[i] == d_in[i];
  if (!same) {
    for (int i = 0; i < 10; i++) g_last_in[i] = d_in[i];
    void* p = nullptr; cudaDriverEntryPointQueryResult qr;
    cudaGetDriverEntryPoint("cuTensorMapEncodeTiled", &p, cudaEnableDefault, &qr);
    g_encode = (PFN_encodeTiled_t)p;
    void *xn, *kk, *vv, *ctx, *hh, *act;
    cudaGetSymbolAddress(&xn, g_xn); cudaGetSymbolAddress(&kk, g_k); cudaGetSymbolAddress(&vv, g_v);
    cudaGetSymbolAddress(&ctx, g_ctx); cudaGetSymbolAddress(&hh, g_h); cudaGetSymbolAddress(&act, g_act);
    map_2d(&g_maps.ckv, d_in[1], SEQ, DM, 128);
    map_3d(&g_maps.wq, d_in[2], DM, HDALL, 64); map_3d(&g_maps.wk, d_in[3], DM, HDALL, 64); map_3d(&g_maps.wv, d_in[4], DM, HDALL, 64);
    map_2d(&g_maps.xn, xn, SEQ, DM, 128);
    map_3d(&g_maps.kst, kk, NH * SEQ, HD, 64); map_3d(&g_maps.vst, vv, NH * SEQ, HD, 64);
    map_3d(&g_maps.kld, kk, NH * SEQ, HD, 128); map_3d(&g_maps.vld, vv, NH * SEQ, HD, 128);
    map_3d(&g_maps.ctxst, ctx, SEQ, HDALL, 64); map_2d(&g_maps.ctxld, ctx, SEQ, HDALL, 128);
    map_3d(&g_maps.wo, d_in[5], HDALL, DM, 64);
    map_2d(&g_maps.h, hh, SEQ, DM, 64);
    map_2d(&g_maps.wg, d_in[7], DM, FF, 64); map_2d(&g_maps.wu, d_in[8], DM, FF, 64);
    map_2d(&g_maps.actst, act, SEQ, FF, 64); map_2d(&g_maps.actld, act, SEQ, FF, 128);
    map_3d(&g_maps.wd, d_in[9], FF, DM, 64);
    cudaFuncSetAttribute(k_mega, cudaFuncAttributeMaxDynamicSharedMemorySize, MK_SMEM);
    g_init = true;
  }
  g_ptrs.x = (const __nv_bfloat16*)d_in[0]; g_ptrs.wg = (const __nv_bfloat16*)d_in[7]; g_ptrs.wu = (const __nv_bfloat16*)d_in[8];
  g_ptrs.wo = (const __nv_bfloat16*)d_in[5]; g_ptrs.wd = (const __nv_bfloat16*)d_in[9]; g_ptrs.out = (__nv_bfloat16*)d_out;
  k_mega<<<128, 384, MK_SMEM, cudaStreamPerThread>>>(g_maps, g_ptrs);
}
```

```cpp
#include <cuda_runtime.h>
#include <cuda_bf16.h>
#include <cuda.h>
#include <stdint.h>

constexpr int SEQ = 2048, DM = 512, NH = 32, HD = 128, HDALL = 4096, FF = 1792;

__device__ __forceinline__ uint32_t smem_u32(const void* p) { return (uint32_t)__cvta_generic_to_shared(p); }
__device__ __forceinline__ void mbar_init(uint32_t bar, uint32_t count) {
  asm volatile("mbarrier.init.shared::cta.b64 [%0], %1;" :: "r"(bar), "r"(count) : "memory");
}
__device__ __forceinline__ void mbar_expect_tx(uint32_t bar, uint32_t bytes) {
  asm volatile("mbarrier.arrive.expect_tx.shared::cta.b64 _, [%0], %1;" :: "r"(bar), "r"(bytes) : "memory");
}
__device__ __forceinline__ void mbar_arrive(uint32_t bar) {
  asm volatile("mbarrier.arrive.shared::cta.b64 _, [%0];" :: "r"(bar) : "memory");
}

#define SPIN_LIMIT "2000000"
#define SPIN_DBG(IDOP, VALOP)
template<int ID> __device__ __forceinline__ void mbar_wait(uint32_t bar, uint32_t parity) {
  asm volatile("{\n.reg .pred p;\n.reg .u32 c;\nmov.u32 c, 0;\n"
    "LAB_WAIT:\n"
    "mbarrier.try_wait.parity.shared::cta.b64 p, [%0], %1;\n"
    "@p bra LAB_DONE;\n"
    "add.u32 c, c, 1;\n"
    SPIN_DBG("%2", "%1")
    "setp.gt.u32 p, c, " SPIN_LIMIT ";\n"
    "@p trap;\n"
    "bra LAB_WAIT;\n"
    "LAB_DONE:\n}" :: "r"(bar), "r"(parity), "n"(ID) : "memory");
}
__device__ __forceinline__ void tma_load_2d(uint32_t dst, const CUtensorMap* m, uint32_t bar, int c0, int c1) {
  asm volatile("cp.async.bulk.tensor.2d.shared::cluster.global.mbarrier::complete_tx::bytes [%0], [%1, {%3, %4}], [%2];"
    :: "r"(dst), "l"(m), "r"(bar), "r"(c0), "r"(c1) : "memory");
}
__device__ __forceinline__ void tma_load_3d(uint32_t dst, const CUtensorMap* m, uint32_t bar, int c0, int c1, int c2) {
  asm volatile("cp.async.bulk.tensor.3d.shared::cluster.global.mbarrier::complete_tx::bytes [%0], [%1, {%3, %4, %5}], [%2];"
    :: "r"(dst), "l"(m), "r"(bar), "r"(c0), "r"(c1), "r"(c2) : "memory");
}
__device__ __forceinline__ void tma_load_5d(uint32_t dst, const CUtensorMap* m, uint32_t bar, int c0, int c1, int c2, int c3, int c4) {
  asm volatile("cp.async.bulk.tensor.5d.shared::cluster.global.mbarrier::complete_tx::bytes [%0], [%1, {%3, %4, %5, %6, %7}], [%2];"
    :: "r"(dst), "l"(m), "r"(bar), "r"(c0), "r"(c1), "r"(c2), "r"(c3), "r"(c4) : "memory");
}
__device__ __forceinline__ void prefetch_tmap(const CUtensorMap* m) {
  asm volatile("prefetch.tensormap [%0];" :: "l"(m) : "memory");
}
__device__ __forceinline__ void wgmma_fence() { asm volatile("wgmma.fence.sync.aligned;" ::: "memory"); }
__device__ __forceinline__ void wgmma_commit() { asm volatile("wgmma.commit_group.sync.aligned;" ::: "memory"); }
template<int N> __device__ __forceinline__ void wgmma_wait() { asm volatile("wgmma.wait_group.sync.aligned %0;" :: "n"(N) : "memory"); }
template<int R> __device__ __forceinline__ void reg_alloc() { asm volatile("setmaxnreg.inc.sync.aligned.u32 %0;" :: "n"(R)); }
template<int R> __device__ __forceinline__ void reg_dealloc() { asm volatile("setmaxnreg.dec.sync.aligned.u32 %0;" :: "n"(R)); }
__device__ __forceinline__ void named_bar_sync(int id, int n) { asm volatile("bar.sync %0, %1;" :: "r"(id), "r"(n) : "memory"); }
__device__ __forceinline__ void named_bar_arrive(int id, int n) { asm volatile("bar.arrive %0, %1;" :: "r"(id), "r"(n) : "memory"); }
__device__ __forceinline__ uint64_t make_desc(uint32_t addr, uint32_t lbo_bytes, uint32_t sbo_bytes) {
  uint64_t d = 0;
  d |= (uint64_t)((addr & 0x3FFFF) >> 4);
  d |= (uint64_t)(lbo_bytes >> 4) << 16;
  d |= (uint64_t)(sbo_bytes >> 4) << 32;
  d |= (uint64_t)1 << 62;
  return d;
}
__device__ __forceinline__ uint32_t desc_lo(uint32_t addr, uint32_t lbo_bytes) { return ((addr & 0x3FFFF) >> 4) + ((lbo_bytes >> 4) << 16); }
template<int N> __device__ __forceinline__ void fence_regs(float (&d)[N]) {
#pragma unroll
  for (int i = 0; i < N; i++) asm volatile("" : "+f"(d[i]) :: "memory");
}
template<int N> __device__ __forceinline__ void fence_regs(uint32_t (&d)[N]) {
#pragma unroll
  for (int i = 0; i < N; i++) asm volatile("" : "+r"(d[i]) :: "memory");
}
__device__ __forceinline__ uint32_t pack_bf16(float lo, float hi) {
  uint32_t r; asm("cvt.rn.bf16x2.f32 %0, %1, %2;" : "=r"(r) : "f"(hi), "f"(lo)); return r;
}
__device__ __forceinline__ float ex2(float x) { float y; asm("ex2.approx.ftz.f32 %0, %1;" : "=f"(y) : "f"(x)); return y; }
__device__ __forceinline__ float bf16lo(uint32_t v) { return __uint_as_float(v << 16); }
__device__ __forceinline__ float bf16hi(uint32_t v) { return __uint_as_float(v & 0xffff0000u); }

__device__ __forceinline__ uint32_t mapa(uint32_t addr, uint32_t cta) {
  uint32_t r; asm("mapa.shared::cluster.u32 %0, %1, %2;" : "=r"(r) : "r"(addr), "r"(cta)); return r;
}
__device__ __forceinline__ void mbar_arrive_cl(uint32_t cluster_addr) {
  asm volatile("mbarrier.arrive.shared::cluster.b64 _, [%0];" :: "r"(cluster_addr) : "memory");
}
template<int ID> __device__ __forceinline__ void mbar_wait_cl(uint32_t bar, uint32_t parity) {
  asm volatile("{\n.reg .pred p;\n.reg .u32 c;\nmov.u32 c, 0;\n"
    "LAB_WAIT:\n"
    "mbarrier.try_wait.parity.acquire.cluster.shared::cta.b64 p, [%0], %1;\n"
    "@p bra LAB_DONE;\n"
    "add.u32 c, c, 1;\n"
    SPIN_DBG("%2", "%1")
    "setp.gt.u32 p, c, " SPIN_LIMIT ";\n"
    "@p trap;\n"
    "bra LAB_WAIT;\n"
    "LAB_DONE:\n}" :: "r"(bar), "r"(parity), "n"(ID) : "memory");
}
__device__ __forceinline__ void tma_load_2d_mc(uint32_t dst, const CUtensorMap* m, uint32_t bar, int c0, int c1) {
  asm volatile("cp.async.bulk.tensor.2d.shared::cluster.global.mbarrier::complete_tx::bytes.multicast::cluster [%0], [%1, {%3, %4}], [%2], %5;"
    :: "r"(dst), "l"(m), "r"(bar), "r"(c0), "r"(c1), "h"((uint16_t)3) : "memory");
}
__device__ __forceinline__ void tma_load_3d_mc(uint32_t dst, const CUtensorMap* m, uint32_t bar, int c0, int c1, int c2) {
  asm volatile("cp.async.bulk.tensor.3d.shared::cluster.global.mbarrier::complete_tx::bytes.multicast::cluster [%0], [%1, {%3, %4, %5}], [%2], %6;"
    :: "r"(dst), "l"(m), "r"(bar), "r"(c0), "r"(c1), "r"(c2), "h"((uint16_t)3) : "memory");
}
__device__ __forceinline__ void tma_store_2d(const CUtensorMap* m, uint32_t src, int c0, int c1) {
  asm volatile("cp.async.bulk.tensor.2d.global.shared::cta.bulk_group [%0, {%2, %3}], [%1];" :: "l"(m), "r"(src), "r"(c0), "r"(c1) : "memory");
}
__device__ __forceinline__ void tma_store_3d(const CUtensorMap* m, uint32_t src, int c0, int c1, int c2) {
  asm volatile("cp.async.bulk.tensor.3d.global.shared::cta.bulk_group [%0, {%2, %3, %4}], [%1];" :: "l"(m), "r"(src), "r"(c0), "r"(c1), "r"(c2) : "memory");
}
__device__ __forceinline__ void bulk_store(void* gdst, uint32_t src, uint32_t bytes) {
  asm volatile("cp.async.bulk.global.shared::cta.bulk_group [%0], [%1], %2;" :: "l"(gdst), "r"(src), "r"(bytes) : "memory");
}
__device__ __forceinline__ void bulk_load(uint32_t dst, const void* gsrc, uint32_t bytes, uint32_t bar) {
  asm volatile("cp.async.bulk.shared::cluster.global.mbarrier::complete_tx::bytes [%0], [%1], %2, [%3];" :: "r"(dst), "l"(gsrc), "r"(bytes), "r"(bar) : "memory");
}
__device__ __forceinline__ void prefetch_3d(const CUtensorMap* m, int c0, int c1, int c2) {
  asm volatile("cp.async.bulk.prefetch.tensor.3d.L2.global [%0, {%1, %2, %3}];" :: "l"(m), "r"(c0), "r"(c1), "r"(c2) : "memory");
}
__device__ __forceinline__ void prefetch_2d(const CUtensorMap* m, int c0, int c1) {
  asm volatile("cp.async.bulk.prefetch.tensor.2d.L2.global [%0, {%1, %2}];" :: "l"(m), "r"(c0), "r"(c1) : "memory");
}
__device__ __forceinline__ void bulk_commit() { asm volatile("cp.async.bulk.commit_group;" ::: "memory"); }
__device__ __forceinline__ void bulk_wait_read() { asm volatile("cp.async.bulk.wait_group.read 0;" ::: "memory"); }
__device__ __forceinline__ void bulk_wait_all() { asm volatile("cp.async.bulk.wait_group 0;" ::: "memory"); }
__device__ __forceinline__ void fence_async_smem() { asm volatile("fence.proxy.async.shared::cta;" ::: "memory"); }
__device__ __forceinline__ void stmatrix_x4(uint32_t addr, uint32_t a, uint32_t b, uint32_t c, uint32_t d) {
  asm volatile("stmatrix.sync.aligned.m8n8.x4.shared.b16 [%0], {%1, %2, %3, %4};" :: "r"(addr), "r"(a), "r"(b), "r"(c), "r"(d) : "memory");
}
__device__ __forceinline__ void st_async_v4(uint32_t raddr, float a, float b, float c, float d, uint32_t rbar) {
  asm volatile("st.async.weak.shared::cluster.mbarrier::complete_tx::bytes.v4.f32 [%0], {%1, %2, %3, %4}, [%5];"
    :: "r"(raddr), "f"(a), "f"(b), "f"(c), "f"(d), "r"(rbar) : "memory");
}
__device__ __forceinline__ float4 lds_v4(uint32_t addr) {
  float4 v; asm volatile("ld.shared.v4.f32 {%0, %1, %2, %3}, [%4];" : "=f"(v.x), "=f"(v.y), "=f"(v.z), "=f"(v.w) : "r"(addr) : "memory"); return v;
}
__device__ __forceinline__ float2 lds_v2(uint32_t addr) {
  float2 v; asm volatile("ld.shared.v2.f32 {%0, %1}, [%2];" : "=f"(v.x), "=f"(v.y) : "r"(addr) : "memory"); return v;
}
__device__ __forceinline__ void sts_v2(uint32_t addr, float a, float b) {
  asm volatile("st.shared.v2.f32 [%0], {%1, %2};" :: "r"(addr), "f"(a), "f"(b) : "memory");
}
__device__ __forceinline__ void flag_arrive(uint32_t* p) {
  asm volatile("red.release.gpu.global.add.u32 [%0], 1;" :: "l"(p) : "memory");
}
__device__ __forceinline__ void flag_arrive_relaxed(uint32_t* p) {
  asm volatile("red.relaxed.gpu.global.add.u32 [%0], 1;" :: "l"(p) : "memory");
}
template<int ID> __device__ __forceinline__ void flag_wait_relaxed(const uint32_t* p, uint32_t target) {
  asm volatile("{\n.reg .pred p;\n.reg .u32 c, v;\nmov.u32 c, 0;\n"
    "LAB_WAIT:\n"
    "ld.relaxed.gpu.global.u32 v, [%0];\n"
    "sub.u32 v, v, %1;\n"
    "setp.ge.s32 p, v, 0;\n"
    "@p bra LAB_DONE;\n"
    "add.u32 c, c, 1;\n"
    SPIN_DBG("%2", "v")
    "setp.gt.u32 p, c, " SPIN_LIMIT ";\n"
    "@p trap;\n"
    "bra LAB_WAIT;\n"
    "LAB_DONE:\n}" :: "l"(p), "r"(target), "n"(ID) : "memory");
}
template<int ID> __device__ __forceinline__ void flag_wait(const uint32_t* p, uint32_t target) {
  asm volatile("{\n.reg .pred p;\n.reg .u32 c, v;\nmov.u32 c, 0;\n"
    "LAB_WAIT:\n"
    "ld.acquire.gpu.global.u32 v, [%0];\n"
    "sub.u32 v, v, %1;\n"
    "setp.ge.s32 p, v, 0;\n"
    "@p bra LAB_DONE;\n"
    "add.u32 c, c, 1;\n"
    SPIN_DBG("%2", "v")
    "setp.gt.u32 p, c, " SPIN_LIMIT ";\n"
    "@p trap;\n"
    "bra LAB_WAIT;\n"
    "LAB_DONE:\n"
    "fence.proxy.async;\n}" :: "l"(p), "r"(target), "n"(ID) : "memory");
}
__device__ __forceinline__ void mbar_expect_only(uint32_t bar, uint32_t bytes) {
  asm volatile("mbarrier.expect_tx.relaxed.cta.shared::cta.b64 [%0], %1;" :: "r"(bar), "r"(bytes) : "memory");
}
__device__ __forceinline__ void prefetch_l2(const void* p, uint32_t bytes) {
  asm volatile("cp.async.bulk.prefetch.L2.global [%0], %1;" :: "l"(p), "r"(bytes) : "memory");
}
__device__ __forceinline__ void cluster_arrive() { asm volatile("barrier.cluster.arrive.release.aligned;" ::: "memory"); }
__device__ __forceinline__ void cluster_wait() { asm volatile("barrier.cluster.wait.acquire.aligned;" ::: "memory"); }

#define PROF_T(k, i)
#define PROF_G(k, i)
#define PROF_INIT()
#define PROF_DUMP()
template<int TB> __device__ __forceinline__ void wgmma_m64n128k16_ss(float (&d)[64], uint32_t da, uint32_t db, int scale_d) {
  asm volatile("{\n.reg .pred p;\n.reg .b64 da, db;\nsetp.ne.b32 p, %66, 0;\nmov.b64 da, {%64, 0x40000040};\nmov.b64 db, {%65, 0x40000040};\n"
    "wgmma.mma_async.sync.aligned.m64n128k16.f32.bf16.bf16 "
    "{%0, %1, %2, %3, %4, %5, %6, %7, %8, %9, %10, %11, %12, %13, %14, %15, "
    "%16, %17, %18, %19, %20, %21, %22, %23, %24, %25, %26, %27, %28, %29, %30, %31, "
    "%32, %33, %34, %35, %36, %37, %38, %39, %40, %41, %42, %43, %44, %45, %46, %47, "
    "%48, %49, %50, %51, %52, %53, %54, %55, %56, %57, %58, %59, %60, %61, %62, %63}, "
    "da, db, p, 1, 1, 0, %67;\n}\n"
    : "+f"(d[0]), "+f"(d[1]), "+f"(d[2]), "+f"(d[3]), "+f"(d[4]), "+f"(d[5]), "+f"(d[6]), "+f"(d[7]), "+f"(d[8]), "+f"(d[9]), "+f"(d[10]), "+f"(d[11]), "+f"(d[12]), "+f"(d[13]), "+f"(d[14]), "+f"(d[15]), "+f"(d[16]), "+f"(d[17]), "+f"(d[18]), "+f"(d[19]), "+f"(d[20]), "+f"(d[21]), "+f"(d[22]), "+f"(d[23]), "+f"(d[24]), "+f"(d[25]), "+f"(d[26]), "+f"(d[27]), "+f"(d[28]), "+f"(d[29]), "+f"(d[30]), "+f"(d[31]), "+f"(d[32]), "+f"(d[33]), "+f"(d[34]), "+f"(d[35]), "+f"(d[36]), "+f"(d[37]), "+f"(d[38]), "+f"(d[39]), "+f"(d[40]), "+f"(d[41]), "+f"(d[42]), "+f"(d[43]), "+f"(d[44]), "+f"(d[45]), "+f"(d[46]), "+f"(d[47]), "+f"(d[48]), "+f"(d[49]), "+f"(d[50]), "+f"(d[51]), "+f"(d[52]), "+f"(d[53]), "+f"(d[54]), "+f"(d[55]), "+f"(d[56]), "+f"(d[57]), "+f"(d[58]), "+f"(d[59]), "+f"(d[60]), "+f"(d[61]), "+f"(d[62]), "+f"(d[63])
    : "r"(da), "r"(db), "r"(scale_d), "n"(TB));
}
template<int TB> __device__ __forceinline__ void wgmma_m64n128k16_rs(float (&d)[64], uint32_t a0, uint32_t a1, uint32_t a2, uint32_t a3, uint32_t db, int scale_d) {
  asm volatile("{\n.reg .pred p;\n.reg .b64 db;\nsetp.ne.b32 p, %69, 0;\nmov.b64 db, {%68, 0x40000040};\n"
    "wgmma.mma_async.sync.aligned.m64n128k16.f32.bf16.bf16 "
    "{%0, %1, %2, %3, %4, %5, %6, %7, %8, %9, %10, %11, %12, %13, %14, %15, "
    "%16, %17, %18, %19, %20, %21, %22, %23, %24, %25, %26, %27, %28, %29, %30, %31, "
    "%32, %33, %34, %35, %36, %37, %38, %39, %40, %41, %42, %43, %44, %45, %46, %47, "
    "%48, %49, %50, %51, %52, %53, %54, %55, %56, %57, %58, %59, %60, %61, %62, %63}, "
    "{%64, %65, %66, %67}, db, p, 1, 1, %70;\n}\n"
    : "+f"(d[0]), "+f"(d[1]), "+f"(d[2]), "+f"(d[3]), "+f"(d[4]), "+f"(d[5]), "+f"(d[6]), "+f"(d[7]), "+f"(d[8]), "+f"(d[9]), "+f"(d[10]), "+f"(d[11]), "+f"(d[12]), "+f"(d[13]), "+f"(d[14]), "+f"(d[15]), "+f"(d[16]), "+f"(d[17]), "+f"(d[18]), "+f"(d[19]), "+f"(d[20]), "+f"(d[21]), "+f"(d[22]), "+f"(d[23]), "+f"(d[24]), "+f"(d[25]), "+f"(d[26]), "+f"(d[27]), "+f"(d[28]), "+f"(d[29]), "+f"(d[30]), "+f"(d[31]), "+f"(d[32]), "+f"(d[33]), "+f"(d[34]), "+f"(d[35]), "+f"(d[36]), "+f"(d[37]), "+f"(d[38]), "+f"(d[39]), "+f"(d[40]), "+f"(d[41]), "+f"(d[42]), "+f"(d[43]), "+f"(d[44]), "+f"(d[45]), "+f"(d[46]), "+f"(d[47]), "+f"(d[48]), "+f"(d[49]), "+f"(d[50]), "+f"(d[51]), "+f"(d[52]), "+f"(d[53]), "+f"(d[54]), "+f"(d[55]), "+f"(d[56]), "+f"(d[57]), "+f"(d[58]), "+f"(d[59]), "+f"(d[60]), "+f"(d[61]), "+f"(d[62]), "+f"(d[63])
    : "r"(a0), "r"(a1), "r"(a2), "r"(a3), "r"(db), "r"(scale_d), "n"(TB));
}
template<int TB> __device__ __forceinline__ void wgmma_m64n256k16_ss(float (&d)[128], uint32_t da, uint32_t db, int scale_d) {
  asm volatile("{\n.reg .pred p;\n.reg .b64 da, db;\nsetp.ne.b32 p, %130, 0;\nmov.b64 da, {%128, 0x40000040};\nmov.b64 db, {%129, 0x40000040};\n"
    "wgmma.mma_async.sync.aligned.m64n256k16.f32.bf16.bf16 "
    "{%0, %1, %2, %3, %4, %5, %6, %7, %8, %9, %10, %11, %12, %13, %14, %15, "
    "%16, %17, %18, %19, %20, %21, %22, %23, %24, %25, %26, %27, %28, %29, %30, %31, "
    "%32, %33, %34, %35, %36, %37, %38, %39, %40, %41, %42, %43, %44, %45, %46, %47, "
    "%48, %49, %50, %51, %52, %53, %54, %55, %56, %57, %58, %59, %60, %61, %62, %63, "
    "%64, %65, %66, %67, %68, %69, %70, %71, %72, %73, %74, %75, %76, %77, %78, %79, "
    "%80, %81, %82, %83, %84, %85, %86, %87, %88, %89, %90, %91, %92, %93, %94, %95, "
    "%96, %97, %98, %99, %100, %101, %102, %103, %104, %105, %106, %107, %108, %109, %110, %111, "
    "%112, %113, %114, %115, %116, %117, %118, %119, %120, %121, %122, %123, %124, %125, %126, %127}, "
    "da, db, p, 1, 1, 0, %131;\n}\n"
    : "+f"(d[0]), "+f"(d[1]), "+f"(d[2]), "+f"(d[3]), "+f"(d[4]), "+f"(d[5]), "+f"(d[6]), "+f"(d[7]), "+f"(d[8]), "+f"(d[9]), "+f"(d[10]), "+f"(d[11]), "+f"(d[12]), "+f"(d[13]), "+f"(d[14]), "+f"(d[15]), "+f"(d[16]), "+f"(d[17]), "+f"(d[18]), "+f"(d[19]), "+f"(d[20]), "+f"(d[21]), "+f"(d[22]), "+f"(d[23]), "+f"(d[24]), "+f"(d[25]), "+f"(d[26]), "+f"(d[27]), "+f"(d[28]), "+f"(d[29]), "+f"(d[30]), "+f"(d[31]), "+f"(d[32]), "+f"(d[33]), "+f"(d[34]), "+f"(d[35]), "+f"(d[36]), "+f"(d[37]), "+f"(d[38]), "+f"(d[39]), "+f"(d[40]), "+f"(d[41]), "+f"(d[42]), "+f"(d[43]), "+f"(d[44]), "+f"(d[45]), "+f"(d[46]), "+f"(d[47]), "+f"(d[48]), "+f"(d[49]), "+f"(d[50]), "+f"(d[51]), "+f"(d[52]), "+f"(d[53]), "+f"(d[54]), "+f"(d[55]), "+f"(d[56]), "+f"(d[57]), "+f"(d[58]), "+f"(d[59]), "+f"(d[60]), "+f"(d[61]), "+f"(d[62]), "+f"(d[63]), "+f"(d[64]), "+f"(d[65]), "+f"(d[66]), "+f"(d[67]), "+f"(d[68]), "+f"(d[69]), "+f"(d[70]), "+f"(d[71]), "+f"(d[72]), "+f"(d[73]), "+f"(d[74]), "+f"(d[75]), "+f"(d[76]), "+f"(d[77]), "+f"(d[78]), "+f"(d[79]), "+f"(d[80]), "+f"(d[81]), "+f"(d[82]), "+f"(d[83]), "+f"(d[84]), "+f"(d[85]), "+f"(d[86]), "+f"(d[87]), "+f"(d[88]), "+f"(d[89]), "+f"(d[90]), "+f"(d[91]), "+f"(d[92]), "+f"(d[93]), "+f"(d[94]), "+f"(d[95]), "+f"(d[96]), "+f"(d[97]), "+f"(d[98]), "+f"(d[99]), "+f"(d[100]), "+f"(d[101]), "+f"(d[102]), "+f"(d[103]), "+f"(d[104]), "+f"(d[105]), "+f"(d[106]), "+f"(d[107]), "+f"(d[108]), "+f"(d[109]), "+f"(d[110]), "+f"(d[111]), "+f"(d[112]), "+f"(d[113]), "+f"(d[114]), "+f"(d[115]), "+f"(d[116]), "+f"(d[117]), "+f"(d[118]), "+f"(d[119]), "+f"(d[120]), "+f"(d[121]), "+f"(d[122]), "+f"(d[123]), "+f"(d[124]), "+f"(d[125]), "+f"(d[126]), "+f"(d[127])
    : "r"(da), "r"(db), "r"(scale_d), "n"(TB));
}
template<int TB> __device__ __forceinline__ void wgmma_m64n96k16_ss(float (&d)[48], uint32_t da, uint32_t db, int scale_d) {
  asm volatile("{\n.reg .pred p;\n.reg .b64 da, db;\nsetp.ne.b32 p, %50, 0;\nmov.b64 da, {%48, 0x40000040};\nmov.b64 db, {%49, 0x40000040};\n"
    "wgmma.mma_async.sync.aligned.m64n96k16.f32.bf16.bf16 "
    "{%0, %1, %2, %3, %4, %5, %6, %7, %8, %9, %10, %11, %12, %13, %14, %15, "
    "%16, %17, %18, %19, %20, %21, %22, %23, %24, %25, %26, %27, %28, %29, %30, %31, "
    "%32, %33, %34, %35, %36, %37, %38, %39, %40, %41, %42, %43, %44, %45, %46, %47}, "
    "da, db, p, 1, 1, 0, %51;\n}\n"
    : "+f"(d[0]), "+f"(d[1]), "+f"(d[2]), "+f"(d[3]), "+f"(d[4]), "+f"(d[5]), "+f"(d[6]), "+f"(d[7]), "+f"(d[8]), "+f"(d[9]), "+f"(d[10]), "+f"(d[11]), "+f"(d[12]), "+f"(d[13]), "+f"(d[14]), "+f"(d[15]), "+f"(d[16]), "+f"(d[17]), "+f"(d[18]), "+f"(d[19]), "+f"(d[20]), "+f"(d[21]), "+f"(d[22]), "+f"(d[23]), "+f"(d[24]), "+f"(d[25]), "+f"(d[26]), "+f"(d[27]), "+f"(d[28]), "+f"(d[29]), "+f"(d[30]), "+f"(d[31]), "+f"(d[32]), "+f"(d[33]), "+f"(d[34]), "+f"(d[35]), "+f"(d[36]), "+f"(d[37]), "+f"(d[38]), "+f"(d[39]), "+f"(d[40]), "+f"(d[41]), "+f"(d[42]), "+f"(d[43]), "+f"(d[44]), "+f"(d[45]), "+f"(d[46]), "+f"(d[47])
    : "r"(da), "r"(db), "r"(scale_d), "n"(TB));
}
__device__ __align__(1024) __nv_bfloat16 g_xn[SEQ * DM];
__device__ __align__(1024) __nv_bfloat16 g_k[NH * SEQ * HD];
__device__ __align__(1024) __nv_bfloat16 g_v[NH * SEQ * HD];
__device__ __align__(1024) __nv_bfloat16 g_ctx[SEQ * HDALL];
__device__ __align__(1024) __nv_bfloat16 g_h[SEQ * DM];
__device__ __align__(1024) __nv_bfloat16 g_act[SEQ * FF];
__device__ __align__(1024) float g_cs[2 * FF];
__device__ __align__(1024) float2 g_stats[16 * 8 * 128];
__device__ __align__(1024) uint32_t g_sync[320 * 8];
__device__ unsigned long long g_ticket;
constexpr int C_XN = 0, C_CS = 16, C_KV = 32, C_CTX = 160, C_H = 224, C_ACT = 240;

struct Softmax { float m0, m1, mc0, mc1, l0, l1; int th0, th1; };
constexpr float SM_C = 0.08838834764831845f * 1.4426950408889634f;
constexpr float SM_TAU = 16.f;

__device__ __forceinline__ void row_max(const float (&s)[64], float& mx0, float& mx1) {
  float a0[4], a1[4];
#pragma unroll
  for (int i = 0; i < 4; i++) { a0[i] = fmaxf(s[4 * i], s[4 * i + 1]); a1[i] = fmaxf(s[4 * i + 2], s[4 * i + 3]); }
#pragma unroll
  for (int j = 4; j < 16; j++) {
    a0[j & 3] = fmaxf(a0[j & 3], fmaxf(s[4 * j], s[4 * j + 1])); a1[j & 3] = fmaxf(a1[j & 3], fmaxf(s[4 * j + 2], s[4 * j + 3]));
  }
  mx0 = fmaxf(fmaxf(a0[0], a0[1]), fmaxf(a0[2], a0[3])); mx1 = fmaxf(fmaxf(a1[0], a1[1]), fmaxf(a1[2], a1[3]));
  mx0 = fmaxf(mx0, __shfl_xor_sync(0xffffffffu, mx0, 1)); mx1 = fmaxf(mx1, __shfl_xor_sync(0xffffffffu, mx1, 1));
  mx0 = fmaxf(mx0, __shfl_xor_sync(0xffffffffu, mx0, 2)); mx1 = fmaxf(mx1, __shfl_xor_sync(0xffffffffu, mx1, 2));
}
__device__ __forceinline__ void sm_set_ref(Softmax& st, float m0, float m1) {
  st.mc0 = m0 * SM_C; st.mc1 = m1 * SM_C;
  const float t0 = m0 + SM_TAU / SM_C, t1 = m1 + SM_TAU / SM_C;
  st.th0 = t0 >= 0.f ? __float_as_int(t0) : (int)0x80000000;
  st.th1 = t1 >= 0.f ? __float_as_int(t1) : (int)0x80000000;
}
__device__ __forceinline__ void sm_first(float (&s)[64], Softmax& st, int row_in_blk, int q) {
#pragma unroll
  for (int j = 0; j < 16; j++) {
    const int c = 8 * j + 2 * q;
    if (c > row_in_blk) s[4 * j] = -INFINITY;
    if (c + 1 > row_in_blk) s[4 * j + 1] = -INFINITY;
    if (c > row_in_blk + 8) s[4 * j + 2] = -INFINITY;
    if (c + 1 > row_in_blk + 8) s[4 * j + 3] = -INFINITY;
  }
  float mx0, mx1;
  row_max(s, mx0, mx1);
  sm_set_ref(st, mx0, mx1);
  st.m0 = mx0; st.m1 = mx1;
  st.l0 = 0.f; st.l1 = 0.f;
}
__device__ __forceinline__ bool sm_next(float (&s)[64], Softmax& st, float& al0, float& al1) {
  int a[4];
#pragma unroll
  for (int i = 0; i < 4; i++) {
    const int o = (i >> 1) * 32 + (i & 1) * 2;
    a[i] = __vimax3_s32(__float_as_int(s[o]), __float_as_int(s[o + 1]), __float_as_int(s[o + 4]));
  }
#pragma unroll
  for (int i = 0; i < 4; i++) {
    const int o = (i >> 1) * 32 + (i & 1) * 2;
    a[i] = __vimax3_s32(a[i], __float_as_int(s[o + 5]), __float_as_int(s[o + 8]));
#pragma unroll
    for (int k = 2; k < 7; k++) a[i] = __vimax3_s32(a[i], __float_as_int(s[o + 4 * k + 1]), __float_as_int(s[o + 4 * k + 4]));
  }
  const int mx0 = __vimax3_s32(a[0], a[2], max(__float_as_int(s[29]), __float_as_int(s[61])));
  const int mx1 = __vimax3_s32(a[1], a[3], max(__float_as_int(s[31]), __float_as_int(s[63])));
  const bool bad = __any_sync(0xffffffffu, mx0 >= st.th0 || mx1 >= st.th1);
  if (bad) {
    float d0, d1;
    row_max(s, d0, d1);
    d0 = fmaxf(d0, st.m0); d1 = fmaxf(d1, st.m1);
    al0 = ex2((st.m0 - d0) * SM_C); al1 = ex2((st.m1 - d1) * SM_C);
    st.m0 = d0; st.m1 = d1;
    sm_set_ref(st, d0, d1);
    st.l0 *= al0; st.l1 *= al1;
  }
  return bad;
}
template<int J0, int J1>
__device__ __forceinline__ void sm_exp(float (&s)[64], const Softmax& st) {
  const float n0 = -st.mc0, n1 = -st.mc1;
#pragma unroll
  for (int j = J0; j < J1; j++) {
    s[4 * j] = ex2(fmaf(s[4 * j], SM_C, n0)); s[4 * j + 1] = ex2(fmaf(s[4 * j + 1], SM_C, n0));
    s[4 * j + 2] = ex2(fmaf(s[4 * j + 2], SM_C, n1)); s[4 * j + 3] = ex2(fmaf(s[4 * j + 3], SM_C, n1));
  }
}
__device__ __forceinline__ void sm_sum_cvt(const float (&s)[64], uint32_t (&p)[32], Softmax& st) {
  float r0 = 0.f, r1 = 0.f, r2 = 0.f, r3 = 0.f;
#pragma unroll
  for (int j = 0; j < 16; j++) { r0 += s[4 * j]; r1 += s[4 * j + 1]; r2 += s[4 * j + 2]; r3 += s[4 * j + 3]; }
  st.l0 += r0 + r1; st.l1 += r2 + r3;
#pragma unroll
  for (int i = 0; i < 32; i++) p[i] = pack_bf16(s[2 * i], s[2 * i + 1]);
}
__device__ __forceinline__ void issue_qk(float (&s)[64], const uint32_t (&qf)[32], uint32_t ks) {
  const uint32_t db = desc_lo(ks, 16);
#pragma unroll
  for (int kk = 0; kk < 8; kk++)
    wgmma_m64n128k16_rs<0>(s, qf[4 * kk], qf[4 * kk + 1], qf[4 * kk + 2], qf[4 * kk + 3], db + (kk >> 2) * 1024 + (kk & 3) * 2, kk != 0);
}
__device__ __forceinline__ void issue_pv(float (&o)[64], const uint32_t (&p)[32], uint32_t vs, int accumulate) {
  const uint32_t db = desc_lo(vs, 16384);
#pragma unroll
  for (int kk = 0; kk < 8; kk++)
    wgmma_m64n128k16_rs<1>(o, p[4 * kk], p[4 * kk + 1], p[4 * kk + 2], p[4 * kk + 3], db + kk * 128, kk == 0 ? accumulate : 1);
}
template<int K0>
__device__ __forceinline__ void issue128(float (&d)[64], uint32_t slot, int wg, bool first) {
  const uint32_t da = desc_lo(slot + wg * 8192, 16), db = desc_lo(slot + 16384, 8192);
#pragma unroll
  for (int k = K0; k < 4; k++) wgmma_m64n128k16_ss<1>(d, da + k * 2, db + k * 128, !(first && k == K0));
}

struct Maps { CUtensorMap ckv, wk, wv, wq, xn, kst, vst, kld, vld, ctxst, ctxld, wo, h, wg, wu, actst, actld, wd; };
struct Ptrs { const __nv_bfloat16 *x, *wg, *wu, *wo, *wd; __nv_bfloat16* out; };

constexpr uint32_t G_ST = 49152, S_ST = 32768;
constexpr uint32_t O_STG = 196608, O_CS = 229376, O_BAR = 231168;
constexpr uint32_t B_GF = O_BAR, B_GE = O_BAR + 32, B_SF = O_BAR + 64, B_SE = O_BAR + 112, B_TF = O_BAR + 160, B_TE = O_BAR + 176,
                   B_XR = O_BAR + 192, B_XF = O_BAR + 208, B_CS = O_BAR + 224;
constexpr int MK_SMEM = 232448;

__device__ __forceinline__ int attn_qblock(int h, int r, int t) {
  return t == 0 ? 15 - r : (t == 1 ? 8 + r : (((t == 2) == ((h & 1) != 0)) ? r : 7 - r));
}

__global__ void __cluster_dims__(2, 1, 1) __launch_bounds__(384, 1)
k_mega(const __grid_constant__ Maps maps, const __grid_constant__ Ptrs ptrs) {
  extern __shared__ __align__(1024) uint8_t smem_raw[];
  const uint32_t sb = smem_u32(smem_raw);
  const int wg = __shfl_sync(0xffffffffu, threadIdx.x >> 7, 0);
  const int b = blockIdx.x, h = b >> 2, r = b & 3, rho = b & 1;
  const int tm = b >> 3, tn = (b >> 1) & 3;
  if (threadIdx.x == 0) {
    for (int s = 0; s < 4; s++) { mbar_init(sb + B_GF + 8 * s, 1); mbar_init(sb + B_GE + 8 * s, 16); }
    for (int s = 0; s < 6; s++) { mbar_init(sb + B_SF + 8 * s, 1); mbar_init(sb + B_SE + 8 * s, 8); }
    for (int s = 0; s < 2; s++) {
      mbar_init(sb + B_TF + 8 * s, 4); mbar_init(sb + B_TE + 8 * s, 1); mbar_init(sb + B_XR + 8 * s, 1); mbar_init(sb + B_XF + 8 * s, 1);
    }
    mbar_init(sb + B_CS, 1);
    asm volatile("fence.mbarrier_init.release.cluster;" ::: "memory");
  }
  PROF_INIT();
  __syncthreads();
  cluster_arrive();
  cluster_wait();

  if (wg == 2) {
    reg_dealloc<40>();
    const int warp = (threadIdx.x >> 5) & 3, lane = threadIdx.x & 31;
    if (warp == 0) {
      if (lane == 0) {
        PROF_G(0, 16);
        const uint32_t ep1 = (uint32_t)(atomicAdd(&g_ticket, 1ULL) >> 7) + 1;
#pragma unroll 1
        for (int f = 0; f < 32; f++) {
          const int st = f & 3, kb = f & 7, mb = (3 - (f >> 3)) * 4 + r;
          const uint32_t bar = sb + B_GF + 8 * st, sa = sb + st * G_ST;
          mbar_wait<1>(sb + B_GE + 8 * st, ((f >> 2) & 1) ^ 1);
          mbar_expect_tx(bar, G_ST);
          tma_load_2d(sa, &maps.ckv, bar, kb * 64, mb * 128);
          tma_load_3d_mc(sa + 16384 + rho * 16384, rho ? &maps.wv : &maps.wk, bar, 0, kb * 64, h * 2);
          if (f == 8) {
            prefetch_3d(&maps.wq, 0, r * 128, h * 2); prefetch_3d(&maps.wq, 0, r * 128 + 64, h * 2);
          }
        }
        int sl = 0; uint32_t ph = 1;
        auto s_acq = [&](uint32_t bytes) -> uint32_t {
          mbar_wait<2>(sb + B_SE + 8 * sl, ph);
          mbar_expect_tx(sb + B_SF + 8 * sl, bytes);
          return sb + sl * S_ST;
        };
        auto s_nxt = [&]() { if (++sl == 6) { sl = 0; ph ^= 1; } };
        auto g_drain = [&](int d, uint32_t par) {
          if (d == 0) mbar_wait<3>(sb + B_GE, par);
          if (d == 1) mbar_wait<3>(sb + B_GE + 8, par);
          if (d == 3) mbar_wait<3>(sb + B_GE + 16, par);
          if (d == 4) mbar_wait<3>(sb + B_GE + 24, par);
        };
#pragma unroll 1
        for (int t = 0; t < 4; t++) {
          const int qb = attn_qblock(h, r, t);
          flag_wait<4>(&g_sync[(C_XN + qb) * 8], ep1 * 24);
          if (t == 0) PROF_T(1, 3);
#pragma unroll 1
          for (int kb = 0; kb < 8; kb++) {
            if (t == 0) g_drain(kb, 1);
            const uint32_t d = s_acq(S_ST), bar = sb + B_SF + 8 * sl;
            tma_load_2d(d, &maps.xn, bar, kb * 64, qb * 128);
            tma_load_3d(d + 16384, &maps.wq, bar, 0, kb * 64, h * 2);
            s_nxt();
          }
          auto ld_kv = [&](const CUtensorMap* mp, int blk) {
            const uint32_t d = s_acq(S_ST);
            tma_load_3d(d, mp, sb + B_SF + 8 * sl, 0, h * SEQ + blk * 128, 0);
            s_nxt();
          };
          if (t == 0) PROF_T(1, 4);
          if (t == 0) flag_wait_relaxed<5>(&g_sync[(C_KV + h * 4) * 8], ep1 * 8);
          if (t == 0) PROF_T(1, 5);
          ld_kv(&maps.kld, qb);
#pragma unroll 1
          for (int j = qb; j > 0; j--) {
            if (t == 0 && (j & 3) == 0) flag_wait_relaxed<5>(&g_sync[(C_KV + h * 4 + 4 - (j >> 2)) * 8], ep1 * 8);
            ld_kv(&maps.kld, j - 1);
            ld_kv(&maps.vld, j);
          }
          ld_kv(&maps.vld, 0);
          if (t == 2) { prefetch_l2(ptrs.wo + b * 32 * DM, 32 * DM * 2); prefetch_l2(ptrs.x + b * 16 * DM, 16 * DM * 2); }
        }
        const int fg = tn * 2 + rho;
        flag_wait<6>(&g_sync[C_CS * 8], ep1 * 128);
        mbar_expect_tx(sb + B_CS, 1792);
        bulk_load(sb + O_CS, g_cs + fg * 224, 896, sb + B_CS);
        bulk_load(sb + O_CS + 896, g_cs + FF + fg * 224, 896, sb + B_CS);
        prefetch_l2(ptrs.wd + b * 14 * DM, 14 * DM * 2);
        {
          const int c1 = tm < 4 ? 1 : 0;
#pragma unroll 1
          for (int kb = 0; kb < 32; kb++) {
            const int cls = (kb >> 4) ^ c1;
            if ((kb & 15) == 0) { PROF_T(1, 6 + (kb >> 4) * 2); flag_wait_relaxed<7>(&g_sync[(C_CTX + (tm * 2 + rho) * 2 + cls) * 8], ep1 * 16); PROF_T(1, 7 + (kb >> 4) * 2); }
            const int k0 = (16 * rho + ((kb >> 1) & 7) * 2 + cls) * 128 + (kb & 1) * 64;
            const uint32_t d = s_acq(S_ST), bar = sb + B_SF + 8 * sl;
            tma_load_2d(d, &maps.ctxld, bar, k0, tm * 128);
            tma_load_3d(d + 16384, &maps.wo, bar, 0, k0, tn * 2);
            s_nxt();
          }
        }
        PROF_T(1, 0);
#pragma unroll 1
        for (int f = 0; f < 16; f++) {
          const int st = f & 3, kb = f & 7, x0 = fg * 224 + (f >> 3) * 128;
          const uint32_t bar = sb + B_GF + 8 * st, sa = sb + st * G_ST;
          mbar_wait<8>(sb + B_GE + 8 * st, (f >> 2) & 1);
          mbar_expect_only(bar, 32768);
          tma_load_2d(sa + 16384, &maps.wg, bar, x0, kb * 64);
          tma_load_2d(sa + 24576, &maps.wg, bar, x0 + 64, kb * 64);
          tma_load_2d(sa + 32768, &maps.wu, bar, x0, kb * 64);
          tma_load_2d(sa + 40960, &maps.wu, bar, x0 + 64, kb * 64);
          if (f >= 3) {
            if (f == 3) {
              PROF_T(1, 10);
              flag_wait_relaxed<9>(&g_sync[(C_H + tm) * 8], ep1 * 16);
              PROF_T(1, 11);
#pragma unroll 1
              for (int i = 0; i < 3; i++) {
                mbar_expect_tx(sb + B_GF + 8 * i, 16384);
                tma_load_2d_mc(sb + i * G_ST + rho * 8192, &maps.h, sb + B_GF + 8 * i, i * 64, tm * 128 + rho * 64);
              }
            }
            mbar_expect_tx(bar, 16384);
            tma_load_2d_mc(sa + rho * 8192, &maps.h, bar, kb * 64, tm * 128 + rho * 64);
          }
        }
        PROF_T(1, 1);
#pragma unroll 1
        for (int d = 0; d < 16; d++) {
          if (d < 6) g_drain(d, 0);
          if ((d & 7) == 0) { PROF_T(1, 12 + (d >> 3) * 2); flag_wait_relaxed<10>(&g_sync[(C_ACT + (tm * 2 + rho) * 2 + (d >> 3)) * 8], ep1 * 8); PROF_T(1, 13 + (d >> 3) * 2); }
          const int k0 = (4 * rho + ((d >> 1) & 3)) * 224 + (d < 8 ? (d & 1) * 64 : 128 + (d & 1) * 32);
          const uint32_t dd = s_acq(S_ST), bar = sb + B_SF + 8 * sl;
          tma_load_2d(dd, &maps.actld, bar, k0, tm * 128);
          tma_load_3d(dd + 16384, &maps.wd, bar, 0, k0, tn * 2);
          s_nxt();
        }
        PROF_T(1, 2);
      }
    } else {
#pragma unroll 1
      for (int i = warp - 1; i < 16; i += 3) {
        const int row = b * 16 + i;
        const uint4* src = reinterpret_cast<const uint4*>(ptrs.x + row * DM);
        const uint4 a = __ldg(src + lane), c = __ldg(src + lane + 32);
        uint32_t w[8] = {a.x, a.y, a.z, a.w, c.x, c.y, c.z, c.w};
        float s = 0.f;
#pragma unroll
        for (int k = 0; k < 8; k++) s += bf16lo(w[k]) + bf16hi(w[k]);
#pragma unroll
        for (int o = 16; o > 0; o >>= 1) s += __shfl_xor_sync(0xffffffffu, s, o);
        const float mean = s * (1.f / 512.f);
        float ss = 0.f;
#pragma unroll
        for (int k = 0; k < 8; k++) { const float u = bf16lo(w[k]) - mean, v = bf16hi(w[k]) - mean; ss += u * u + v * v; }
#pragma unroll
        for (int o = 16; o > 0; o >>= 1) ss += __shfl_xor_sync(0xffffffffu, ss, o);
        const float rstd = rsqrtf(ss * (1.f / 512.f) + 1e-5f);
#pragma unroll
        for (int k = 0; k < 8; k++) w[k] = pack_bf16((bf16lo(w[k]) - mean) * rstd, (bf16hi(w[k]) - mean) * rstd);
        uint4* dst = reinterpret_cast<uint4*>(g_xn + row * DM);
        dst[lane] = make_uint4(w[0], w[1], w[2], w[3]);
        dst[lane + 32] = make_uint4(w[4], w[5], w[6], w[7]);
      }
      __syncwarp();
      if (lane == 0) flag_arrive(&g_sync[(C_XN + (b >> 3)) * 8]);
      if (warp == 3) {
        if (lane < 28) {
          const int cp = lane % 14, hf = lane / 14;
          const uint32_t* src = reinterpret_cast<const uint32_t*>((b < 64 ? ptrs.wg : ptrs.wu) + (size_t)hf * 256 * FF + (b & 63) * 28 + cp * 2);
          float s0 = 0.f, s1 = 0.f;
#pragma unroll 8
          for (int k = 0; k < 256; k++) { const uint32_t v = __ldg(src + k * (FF / 2)); s0 += bf16lo(v); s1 += bf16hi(v); }
          const float t0 = __shfl_down_sync(0x0fffffffu, s0, 14), t1 = __shfl_down_sync(0x0fffffffu, s1, 14);
          if (lane < 14) *reinterpret_cast<float2*>(g_cs + b * 28 + cp * 2) = make_float2(s0 + t0, s1 + t1);
        }
        __syncwarp();
        if (lane == 0) flag_arrive(&g_sync[C_CS * 8]);
      } else if (lane == 0) {
        const int w = warp - 1;
        const uint32_t stg = sb + O_STG + w * 16384;
        const uint32_t xr_peer = mapa(sb + B_XR + 8 * w, rho ^ 1);
#pragma unroll 1
        for (int job = 0; job < 15; job++) {
          mbar_wait<11>(sb + B_TF + 8 * w, job & 1);
          if (w == 0) PROF_T(3, job);
          uint32_t* flag = nullptr;
          if (job < 8) {
            const int i = job >> 1;
            tma_store_3d((job & 1) ? &maps.vst : &maps.kst, stg, 0, h * SEQ + ((3 - i) * 4 + r) * 128 + w * 64, 0);
            if (job & 1) flag = &g_sync[(C_KV + h * 4 + i) * 8];
          } else if (job < 12) {
            const int qb = attn_qblock(h, r, job - 8);
            tma_store_3d(&maps.ctxst, stg, 0, qb * 128 + w * 64, h * 2);
            flag = &g_sync[(C_CTX + (qb * 2 + (h >> 4)) * 2 + (h & 1)) * 8];
          } else if (job == 12) {
            tma_store_2d(&maps.h, stg, tn * 128 + rho * 64, tm * 128 + w * 64);
            bulk_store(g_stats + (tm * 8 + tn * 2 + rho) * 128 + w * 64, stg + 8192, 512);
            flag = &g_sync[(C_H + tm) * 8];
          } else {
            const int x0 = (tn * 2 + rho) * 224 + (job - 13) * 128;
            tma_store_2d(&maps.actst, stg, x0, tm * 128 + w * 64);
            tma_store_2d(&maps.actst, stg + 8192, x0 + (job == 13 ? 64 : 32), tm * 128 + w * 64);
            flag = &g_sync[(C_ACT + (tm * 2 + (tn >> 1)) * 2 + (job - 13)) * 8];
          }
          bulk_commit();
          bulk_wait_read();
          if (w == 0) PROF_T(4, job);
          mbar_arrive(sb + B_TE + 8 * w);
          if (job == 11 || job == 14) mbar_arrive_cl(xr_peer);
          if (flag) { bulk_wait_all(); if (w == 0) PROF_T(5, job); flag_arrive_relaxed(flag); }
          if (w == 0) PROF_T(2, job);
        }
      }
    }
    __syncwarp();
    PROF_DUMP();
    cluster_arrive();
    cluster_wait();
  } else {
    reg_alloc<232>();
    const int lane = threadIdx.x & 31, warp = (threadIdx.x >> 5) & 3, q = lane & 3;
    const int row_in_blk = wg * 64 + warp * 16 + (lane >> 2);
    const uint32_t stg = sb + O_STG + wg * 16384;
    const uint32_t stm = stg + (warp * 16 + (lane & 7) + ((lane >> 3) & 1) * 8) * 128 + (((lane >> 4) ^ (lane & 7)) << 4);
    const uint32_t ge_cl = mapa(sb + B_GE, (lane & 1) ^ rho);
    auto g_release = [&](int st) { if (lane < 2) mbar_arrive_cl(ge_cl + 8 * st); };
    uint32_t jpar = 1;
    auto stg_acquire = [&]() { mbar_wait<20>(sb + B_TE + 8 * wg, jpar); jpar ^= 1; };
    auto stg_publish = [&]() { fence_async_smem(); __syncwarp(); if (lane == 0) mbar_arrive(sb + B_TF + 8 * wg); };
    auto stg_put = [&](int atom, int jp, uint32_t a, uint32_t c, uint32_t d, uint32_t e) {
      stmatrix_x4((stm + atom * 8192) ^ (((2 * jp) & 7) << 4), a, c, d, e);
    };
    if (threadIdx.x == 0) PROF_T(0, 0);

    int sl = 0; uint32_t ph = 0;
    auto s_nxt = [&]() { if (++sl == 6) { sl = 0; ph ^= 1; } };
    auto s_release = [&](int a) { if (lane == 0) mbar_arrive(sb + B_SE + 8 * a); };
    float s[64];
    uint32_t qf[32];
    {
      float acc[128];
      uint32_t pk[64];
      auto put_tile = [&](int half) {
        stg_acquire();
#pragma unroll
        for (int jp = 0; jp < 8; jp++)
          stg_put(jp >> 2, jp, pk[half * 32 + 4 * jp], pk[half * 32 + 4 * jp + 1], pk[half * 32 + 4 * jp + 2], pk[half * 32 + 4 * jp + 3]);
        stg_publish();
      };
#pragma unroll
      for (int i = 0; i < 64; i++) pk[i] = 0;
      for (int i = 0; i < 4; i++) {
#pragma unroll
        for (int kb = 0; kb < 8; kb++) {
          const int st = kb & 3;
          mbar_wait<21>(sb + B_GF + 8 * st, (kb >> 2) & 1);
          const uint32_t da = desc_lo(sb + st * G_ST + wg * 8192, 16), db = desc_lo(sb + st * G_ST + 16384, 8192);
          wgmma_fence();
#pragma unroll
          for (int k = 0; k < 4; k++) wgmma_m64n256k16_ss<1>(acc, da + k * 2, db + k * 128, (kb | k) != 0);
          wgmma_commit();
          if (kb > 0) { wgmma_wait<1>(); g_release((kb - 1) & 3); }
          if (kb == 0 && i > 0) put_tile(0);
          if (kb == 4 && i > 0) put_tile(1);
        }
        wgmma_wait<0>();
        g_release(3);
        fence_regs(acc);
#pragma unroll
        for (int k = 0; k < 64; k++) pk[k] = pack_bf16(acc[2 * k], acc[2 * k + 1]);
        if (threadIdx.x == 0) PROF_T(0, 1 + i);
      }
      int prev = 0;
#pragma unroll
      for (int kb = 0; kb < 8; kb++) {
        mbar_wait<22>(sb + B_SF + 8 * sl, ph);
        wgmma_fence();
        issue128<0>(s, sb + sl * S_ST, wg, kb == 0);
        wgmma_commit();
        if (kb > 0) { wgmma_wait<1>(); s_release(prev); }
        prev = sl; s_nxt();
        if (kb == 0) put_tile(0);
        if (kb == 4) put_tile(1);
      }
      wgmma_wait<0>();
      fence_regs(s);
      s_release(prev);
#pragma unroll
      for (int k = 0; k < 32; k++) qf[k] = pack_bf16(s[2 * k], s[2 * k + 1]);
    }
    if (threadIdx.x == 0) PROF_T(0, 5);
    {
      float o[64]; uint32_t p[32];
      Softmax st; float al0 = 1.f, al1 = 1.f;
#pragma unroll
      for (int i = 0; i < 64; i++) o[i] = 0.f;
      if (wg == 1) named_bar_arrive(1, 256);
      for (int t = 0; t < 4; t++) {
        const int qb = attn_qblock(h, r, t);
        if (threadIdx.x == 0) PROF_T(6, t);
        mbar_wait<23>(sb + B_SF + 8 * sl, ph);
        if (threadIdx.x == 0) PROF_T(6, 4 + t);
        named_bar_sync(1 + wg, 256);
        wgmma_fence();
        issue_qk(s, qf, sb + sl * S_ST);
        wgmma_commit();
        named_bar_arrive(2 - wg, 256);
        wgmma_wait<0>(); fence_regs(s);
        s_release(sl); s_nxt();
        sm_first(s, st, row_in_blk, q);
        sm_exp<0, 16>(s, st);
        sm_sum_cvt(s, p, st);
        mbar_wait<24>(sb + B_SF + 8 * sl, ph);
        if (threadIdx.x == 0) PROF_T(6, 8 + t);
        for (int j = qb; j > 0; j--) {
          const int ks = sl; s_nxt();
          const int vs = sl;
          named_bar_sync(1 + wg, 256);
          wgmma_fence();
          issue_qk(s, qf, sb + ks * S_ST);
          wgmma_commit();
          mbar_wait<25>(sb + B_SF + 8 * vs, ph);
          s_nxt();
          wgmma_fence();
          issue_pv(o, p, sb + vs * S_ST, j != qb);
          wgmma_commit();
          named_bar_arrive(2 - wg, 256);
          wgmma_wait<1>(); fence_regs(s);
          s_release(ks);
          const bool bad = sm_next(s, st, al0, al1);
          sm_exp<0, 4>(s, st);
          fence_regs(s);
          mbar_wait<26>(sb + B_SF + 8 * sl, ph);
          wgmma_wait<0>(); fence_regs(o); fence_regs(p);
          s_release(vs);
          if (bad) {
#pragma unroll
            for (int i = 0; i < 16; i++) { o[4 * i] *= al0; o[4 * i + 1] *= al0; o[4 * i + 2] *= al1; o[4 * i + 3] *= al1; }
          }
          sm_exp<4, 16>(s, st);
          sm_sum_cvt(s, p, st);
        }
        if (threadIdx.x == 0) PROF_T(0, 6 + t);
        const int vs = sl; s_nxt();
        named_bar_sync(1 + wg, 256);
        wgmma_fence();
        issue_pv(o, p, sb + vs * S_ST, qb != 0);
        wgmma_commit();
        if (t < 3 || wg == 0) named_bar_arrive(2 - wg, 256);
        float l0 = st.l0, l1 = st.l1;
        const int nkb = t < 3 ? 8 : 32;
        mbar_wait<27>(sb + B_SF + 8 * sl, ph);
        wgmma_fence();
        issue128<0>(s, sb + sl * S_ST, wg, true);
        wgmma_commit();
        int prev = sl; s_nxt();
        l0 += __shfl_xor_sync(0xffffffffu, l0, 1); l1 += __shfl_xor_sync(0xffffffffu, l1, 1);
        l0 += __shfl_xor_sync(0xffffffffu, l0, 2); l1 += __shfl_xor_sync(0xffffffffu, l1, 2);
        const float i0 = 1.f / l0, i1 = 1.f / l1;
        wgmma_wait<1>(); fence_regs(o); fence_regs(p);
        s_release(vs);
        auto put_ctx = [&](int jp) {
          stg_put(jp >> 2, jp, pack_bf16(o[8 * jp] * i0, o[8 * jp + 1] * i0), pack_bf16(o[8 * jp + 2] * i1, o[8 * jp + 3] * i1),
                  pack_bf16(o[8 * jp + 4] * i0, o[8 * jp + 5] * i0), pack_bf16(o[8 * jp + 6] * i1, o[8 * jp + 7] * i1));
        };
        stg_acquire();
        put_ctx(0); put_ctx(1);
        mbar_wait<28>(sb + B_SF + 8 * sl, ph);
        wgmma_fence();
        issue128<0>(s, sb + sl * S_ST, wg, false);
        wgmma_commit();
        put_ctx(2); put_ctx(3); put_ctx(4);
        wgmma_wait<1>(); s_release(prev); prev = sl; s_nxt();
        mbar_wait<28>(sb + B_SF + 8 * sl, ph);
        wgmma_fence();
        issue128<0>(s, sb + sl * S_ST, wg, false);
        wgmma_commit();
        put_ctx(5); put_ctx(6); put_ctx(7);
        stg_publish();
        wgmma_wait<1>(); s_release(prev); prev = sl; s_nxt();
        for (int kb = 3; kb < nkb; kb++) {
          mbar_wait<29>(sb + B_SF + 8 * sl, ph);
          wgmma_fence();
          issue128<0>(s, sb + sl * S_ST, wg, false);
          wgmma_commit();
          wgmma_wait<1>(); s_release(prev); prev = sl; s_nxt();
        }
        wgmma_wait<0>();
        fence_regs(s);
        s_release(prev);
#pragma unroll
        for (int k = 0; k < 32; k++) qf[k] = pack_bf16(s[2 * k], s[2 * k + 1]);
      }
    }
    if (threadIdx.x == 0) PROF_T(0, 10);
#pragma unroll
    for (int st = 0; st < 4; st++) g_release(st);
    uint32_t xr[16];
    {
      const uint32_t* xs = reinterpret_cast<const uint32_t*>(ptrs.x + (tm * 128 + row_in_blk) * DM + tn * 128 + rho * 64 + 2 * q);
#pragma unroll
      for (int j = 0; j < 8; j++) { xr[2 * j] = __ldg(xs + 4 * j); xr[2 * j + 1] = __ldg(xs + 8 * (DM / 2) + 4 * j); }
    }

    const uint32_t xbuf = stg + (threadIdx.x & 127) * 16;
    const uint32_t xbuf_peer = mapa(xbuf, rho ^ 1), xf_peer = mapa(sb + B_XF + 8 * wg, rho ^ 1);
    auto exchange = [&](float (&d)[64], float (&v)[32], uint32_t par) {
      if ((threadIdx.x & 127) == 0) mbar_expect_tx(sb + B_XF + 8 * wg, 16384);
      mbar_wait_cl<30>(sb + B_XR + 8 * wg, par);
#pragma unroll
      for (int i = 0; i < 8; i++)
        st_async_v4(xbuf_peer + i * 2048, rho ? d[4 * i] : d[32 + 4 * i], rho ? d[4 * i + 1] : d[33 + 4 * i],
                    rho ? d[4 * i + 2] : d[34 + 4 * i], rho ? d[4 * i + 3] : d[35 + 4 * i], xf_peer);
#pragma unroll
      for (int i = 0; i < 32; i++) v[i] = rho ? d[32 + i] : d[i];
    };
    auto exchange_finish = [&](float (&v)[32], uint32_t par) {
      mbar_wait_cl<31>(sb + B_XF + 8 * wg, par);
#pragma unroll
      for (int i = 0; i < 8; i++) {
        const float4 u = lds_v4(xbuf + i * 2048);
        v[4 * i] += u.x; v[4 * i + 1] += u.y; v[4 * i + 2] += u.z; v[4 * i + 3] += u.w;
      }
    };
    {
      float v[32];
      exchange(s, v, 0);
      stg_acquire();
      exchange_finish(v, 0);
      uint32_t hp[16];
      float s0 = 0.f, s1 = 0.f;
#pragma unroll
      for (int j = 0; j < 8; j++) {
        hp[2 * j] = pack_bf16(bf16lo(xr[2 * j]) + v[4 * j], bf16hi(xr[2 * j]) + v[4 * j + 1]);
        hp[2 * j + 1] = pack_bf16(bf16lo(xr[2 * j + 1]) + v[4 * j + 2], bf16hi(xr[2 * j + 1]) + v[4 * j + 3]);
        s0 += bf16lo(hp[2 * j]) + bf16hi(hp[2 * j]); s1 += bf16lo(hp[2 * j + 1]) + bf16hi(hp[2 * j + 1]);
      }
      named_bar_sync(3 + wg, 128);
#pragma unroll
      for (int jp = 0; jp < 4; jp++) stg_put(0, jp, hp[4 * jp], hp[4 * jp + 1], hp[4 * jp + 2], hp[4 * jp + 3]);
      s0 += __shfl_xor_sync(0xffffffffu, s0, 1); s1 += __shfl_xor_sync(0xffffffffu, s1, 1);
      s0 += __shfl_xor_sync(0xffffffffu, s0, 2); s1 += __shfl_xor_sync(0xffffffffu, s1, 2);
      s0 *= (1.f / 64.f); s1 *= (1.f / 64.f);
      float m0 = 0.f, m1 = 0.f;
#pragma unroll
      for (int j = 0; j < 8; j++) {
        const float a = bf16lo(hp[2 * j]) - s0, c = bf16hi(hp[2 * j]) - s0, d = bf16lo(hp[2 * j + 1]) - s1, e = bf16hi(hp[2 * j + 1]) - s1;
        m0 += a * a + c * c; m1 += d * d + e * e;
      }
      m0 += __shfl_xor_sync(0xffffffffu, m0, 1); m1 += __shfl_xor_sync(0xffffffffu, m1, 1);
      m0 += __shfl_xor_sync(0xffffffffu, m0, 2); m1 += __shfl_xor_sync(0xffffffffu, m1, 2);
      if (q == 0) {
        const uint32_t a = stg + 8192 + (warp * 16 + (lane >> 2)) * 8;
        sts_v2(a, s0, m0); sts_v2(a + 64, s1, m1);
      }
      stg_publish();
    }
    if (threadIdx.x == 0) PROF_T(0, 11);
    {
      float mu0, mu1, rs0, rs1;
      uint32_t pg[32], pu[32];
      const uint32_t csb = sb + O_CS + q * 8;
      {
        float acc[128];
#pragma unroll
        for (int kb = 0; kb < 8; kb++) {
          const int st = kb & 3;
          mbar_wait<32>(sb + B_GF + 8 * st, (kb >> 2) & 1);
          const uint32_t da = desc_lo(sb + st * G_ST + wg * 8192, 16), db = desc_lo(sb + st * G_ST + 16384, 8192);
          wgmma_fence();
#pragma unroll
          for (int k = 0; k < 4; k++) wgmma_m64n256k16_ss<1>(acc, da + k * 2, db + k * 128, (kb | k) != 0);
          wgmma_commit();
          if (kb > 0) { wgmma_wait<1>(); g_release((kb - 1) & 3); }
          if (kb == 0) {
            const float2* sp = g_stats + (tm * 8 + 2 * q) * 128 + row_in_blk;
            const float2 a0 = __ldcg(sp), a1 = __ldcg(sp + 128), c0 = __ldcg(sp + 8), c1 = __ldcg(sp + 136);
            float t0 = a0.x + a1.x, t1 = c0.x + c1.x;
            t0 += __shfl_xor_sync(0xffffffffu, t0, 1); t1 += __shfl_xor_sync(0xffffffffu, t1, 1);
            t0 += __shfl_xor_sync(0xffffffffu, t0, 2); t1 += __shfl_xor_sync(0xffffffffu, t1, 2);
            mu0 = t0 * 0.125f; mu1 = t1 * 0.125f;
            float v0 = a0.y + a1.y + 64.f * ((a0.x - mu0) * (a0.x - mu0) + (a1.x - mu0) * (a1.x - mu0));
            float v1 = c0.y + c1.y + 64.f * ((c0.x - mu1) * (c0.x - mu1) + (c1.x - mu1) * (c1.x - mu1));
            v0 += __shfl_xor_sync(0xffffffffu, v0, 1); v1 += __shfl_xor_sync(0xffffffffu, v1, 1);
            v0 += __shfl_xor_sync(0xffffffffu, v0, 2); v1 += __shfl_xor_sync(0xffffffffu, v1, 2);
            rs0 = rsqrtf(v0 * (1.f / 512.f) + 1e-5f); rs1 = rsqrtf(v1 * (1.f / 512.f) + 1e-5f);
          }
        }
        wgmma_wait<0>();
        g_release(3);
        fence_regs(acc);
        mbar_wait<33>(sb + B_CS, 0);
#pragma unroll
        for (int j = 0; j < 16; j++) {
          const float2 cg = lds_v2(csb + j * 32), cu = lds_v2(csb + 896 + j * 32);
          pg[2 * j] = pack_bf16(rs0 * fmaf(-mu0, cg.x, acc[4 * j]), rs0 * fmaf(-mu0, cg.y, acc[4 * j + 1]));
          pg[2 * j + 1] = pack_bf16(rs1 * fmaf(-mu1, cg.x, acc[4 * j + 2]), rs1 * fmaf(-mu1, cg.y, acc[4 * j + 3]));
          pu[2 * j] = pack_bf16(rs0 * fmaf(-mu0, cu.x, acc[64 + 4 * j]), rs0 * fmaf(-mu0, cu.y, acc[64 + 4 * j + 1]));
          pu[2 * j + 1] = pack_bf16(rs1 * fmaf(-mu1, cu.x, acc[64 + 4 * j + 2]), rs1 * fmaf(-mu1, cu.y, acc[64 + 4 * j + 3]));
        }
      }
      if (threadIdx.x == 0) PROF_T(0, 12);
      auto glu = [&](uint32_t g, uint32_t u) -> uint32_t {
        const float a = __fdividef(bf16lo(u), 1.f + ex2(-1.4426950408889634f * bf16lo(g)));
        const float c = __fdividef(bf16hi(u), 1.f + ex2(-1.4426950408889634f * bf16hi(g)));
        return pack_bf16(a, c);
      };
      uint32_t rg[24], ru[24];
      {
        float ag[48], au[48];
#pragma unroll
        for (int kb = 0; kb < 8; kb++) {
          const int st = kb & 3;
          mbar_wait<34>(sb + B_GF + 8 * st, (kb >> 2) & 1);
          const uint32_t da = desc_lo(sb + st * G_ST + wg * 8192, 16), db = desc_lo(sb + st * G_ST + 16384, 8192);
          wgmma_fence();
#pragma unroll
          for (int k = 0; k < 4; k++) {
            wgmma_m64n96k16_ss<1>(ag, da + k * 2, db + k * 128, (kb | k) != 0);
            wgmma_m64n96k16_ss<1>(au, da + k * 2, db + 1024 + k * 128, (kb | k) != 0);
          }
          wgmma_commit();
          if (kb == 0) stg_acquire();
          if (kb < 4) {
#pragma unroll
            for (int jp = 2 * kb; jp < 2 * kb + 2; jp++)
              stg_put(jp >> 2, jp, glu(pg[4 * jp], pu[4 * jp]), glu(pg[4 * jp + 1], pu[4 * jp + 1]),
                      glu(pg[4 * jp + 2], pu[4 * jp + 2]), glu(pg[4 * jp + 3], pu[4 * jp + 3]));
          }
          if (kb == 3) stg_publish();
          if (kb > 0) { wgmma_wait<1>(); g_release((kb - 1) & 3); }
        }
        wgmma_wait<0>();
        g_release(3);
        fence_regs(ag); fence_regs(au);
        if (lane == 0) PROF_T(7, wg * 4 + warp);
#pragma unroll
        for (int j = 0; j < 12; j++) {
          const float2 cg = lds_v2(csb + 512 + j * 32), cu = lds_v2(csb + 896 + 512 + j * 32);
          rg[2 * j] = pack_bf16(rs0 * fmaf(-mu0, cg.x, ag[4 * j]), rs0 * fmaf(-mu0, cg.y, ag[4 * j + 1]));
          rg[2 * j + 1] = pack_bf16(rs1 * fmaf(-mu1, cg.x, ag[4 * j + 2]), rs1 * fmaf(-mu1, cg.y, ag[4 * j + 3]));
          ru[2 * j] = pack_bf16(rs0 * fmaf(-mu0, cu.x, au[4 * j]), rs0 * fmaf(-mu0, cu.y, au[4 * j + 1]));
          ru[2 * j + 1] = pack_bf16(rs1 * fmaf(-mu1, cu.x, au[4 * j + 2]), rs1 * fmaf(-mu1, cu.y, au[4 * j + 3]));
        }
      }
      if (threadIdx.x == 0) PROF_T(0, 13);
      fence_regs(rg); fence_regs(ru);
      if (lane == 0) PROF_T(7, 8 + wg * 4 + warp);
      stg_acquire();
#pragma unroll
      for (int jp = 0; jp < 6; jp++) {
        const uint32_t a = glu(rg[4 * jp], ru[4 * jp]), c = glu(rg[4 * jp + 1], ru[4 * jp + 1]);
        const uint32_t d = glu(rg[4 * jp + 2], ru[4 * jp + 2]), e = glu(rg[4 * jp + 3], ru[4 * jp + 3]);
        if (jp < 4) stg_put(0, jp, a, c, d, e);
        if (jp >= 2) stg_put(1, jp - 2, a, c, d, e);
      }
      stg_publish();
      if (lane == 0) PROF_T(7, 16 + wg * 4 + warp);
      uint32_t hr[16];
      mbar_wait<35>(sb + B_SF + 8 * sl, ph);
      wgmma_fence();
      issue128<0>(s, sb + sl * S_ST, wg, true);
      wgmma_commit();
      int prev = sl; s_nxt();
#pragma unroll 1
      for (int kb = 1; kb < 8; kb++) {
        mbar_wait<35>(sb + B_SF + 8 * sl, ph);
        wgmma_fence();
        issue128<0>(s, sb + sl * S_ST, wg, false);
        wgmma_commit();
        wgmma_wait<1>(); s_release(prev);
        prev = sl; s_nxt();
      }
      {
        const uint32_t* hs = reinterpret_cast<const uint32_t*>(g_h + (tm * 128 + row_in_blk) * DM + tn * 128 + rho * 64 + 2 * q);
#pragma unroll
        for (int j = 0; j < 8; j++) { hr[2 * j] = __ldcg(hs + 4 * j); hr[2 * j + 1] = __ldcg(hs + 8 * (DM / 2) + 4 * j); }
      }
#pragma unroll 1
      for (int g = 0; g < 4; g++) {
        mbar_wait<36>(sb + B_SF + 8 * sl, ph);
        wgmma_fence();
        issue128<0>(s, sb + sl * S_ST, wg, false);
        wgmma_commit();
        wgmma_wait<1>(); s_release(prev); prev = sl; s_nxt();
        mbar_wait<37>(sb + B_SF + 8 * sl, ph);
        wgmma_fence();
        issue128<2>(s, sb + sl * S_ST, wg, false);
        wgmma_commit();
        wgmma_wait<1>(); s_release(prev); prev = sl; s_nxt();
      }
      wgmma_wait<0>();
      fence_regs(s);
      s_release(prev);
      if (threadIdx.x == 0) PROF_T(0, 14);
      float v[32];
      exchange(s, v, 1);
      exchange_finish(v, 1);
      uint32_t* dst = reinterpret_cast<uint32_t*>(ptrs.out + (tm * 128 + row_in_blk) * DM + tn * 128 + rho * 64 + 2 * q);
#pragma unroll
      for (int j = 0; j < 8; j++) {
        dst[4 * j] = pack_bf16(bf16lo(hr[2 * j]) + v[4 * j], bf16hi(hr[2 * j]) + v[4 * j + 1]);
        dst[8 * (DM / 2) + 4 * j] = pack_bf16(bf16lo(hr[2 * j + 1]) + v[4 * j + 2], bf16hi(hr[2 * j + 1]) + v[4 * j + 3]);
      }
    }
    if (threadIdx.x == 0) { PROF_T(0, 15); PROF_G(0, 17); }
    PROF_DUMP();
    cluster_arrive();
    cluster_wait();
  }
}

typedef CUresult (*PFN_encodeTiled_t)(CUtensorMap*, CUtensorMapDataType, cuuint32_t, void*, const cuuint64_t*, const cuuint64_t*,
                                      const cuuint32_t*, const cuuint32_t*, CUtensorMapInterleave, CUtensorMapSwizzle,
                                      CUtensorMapL2promotion, CUtensorMapFloatOOBfill);
static PFN_encodeTiled_t g_encode = nullptr;
static void make_map(CUtensorMap* m, const void* base, int rank, const cuuint64_t* dims, const cuuint64_t* strides, const cuuint32_t* box) {
  cuuint32_t es[5] = {1, 1, 1, 1, 1};
  g_encode(m, CU_TENSOR_MAP_DATA_TYPE_BFLOAT16, rank, const_cast<void*>(base), dims, strides, box, es, CU_TENSOR_MAP_INTERLEAVE_NONE,
           CU_TENSOR_MAP_SWIZZLE_128B, CU_TENSOR_MAP_L2_PROMOTION_L2_256B, CU_TENSOR_MAP_FLOAT_OOB_FILL_NONE);
}
static void map_2d(CUtensorMap* m, const void* base, int rows, int cols, int brows) {
  cuuint64_t d[2] = {(cuuint64_t)cols, (cuuint64_t)rows}, s[1] = {(cuuint64_t)cols * 2}; cuuint32_t b[2] = {64, (cuuint32_t)brows};
  make_map(m, base, 2, d, s, b);
}
static void map_3d(CUtensorMap* m, const void* base, int rows, int cols, int brows) {
  cuuint64_t d[3] = {64, (cuuint64_t)rows, (cuuint64_t)(cols / 64)}, s[2] = {(cuuint64_t)cols * 2, 128}; cuuint32_t b[3] = {64, (cuuint32_t)brows, 2};
  make_map(m, base, 3, d, s, b);
}

static Maps g_maps;
static Ptrs g_ptrs;
static bool g_init = false;
static void* g_last_in[10];

extern "C" void kernel_launch(void* const* d_in, const int* in_sizes, int n_in, void* d_out, int out_size) {
  bool same = g_init;
  for (int i = 0; i < 10; i++) same = same && g_last_in[i] == d_in[i];
  if (!same) {
    for (int i = 0; i < 10; i++) g_last_in[i] = d_in[i];
    void* p = nullptr; cudaDriverEntryPointQueryResult qr;
    cudaGetDriverEntryPoint("cuTensorMapEncodeTiled", &p, cudaEnableDefault, &qr);
    g_encode = (PFN_encodeTiled_t)p;
    void *xn, *kk, *vv, *ctx, *hh, *act;
    cudaGetSymbolAddress(&xn, g_xn); cudaGetSymbolAddress(&kk, g_k); cudaGetSymbolAddress(&vv, g_v);
    cudaGetSymbolAddress(&ctx, g_ctx); cudaGetSymbolAddress(&hh, g_h); cudaGetSymbolAddress(&act, g_act);
    map_2d(&g_maps.ckv, d_in[1], SEQ, DM, 128);
    map_3d(&g_maps.wq, d_in[2], DM, HDALL, 64); map_3d(&g_maps.wk, d_in[3], DM, HDALL, 64); map_3d(&g_maps.wv, d_in[4], DM, HDALL, 64);
    map_2d(&g_maps.xn, xn, SEQ, DM, 128);
    map_3d(&g_maps.kst, kk, NH * SEQ, HD, 64); map_3d(&g_maps.vst, vv, NH * SEQ, HD, 64);
    map_3d(&g_maps.kld, kk, NH * SEQ, HD, 128); map_3d(&g_maps.vld, vv, NH * SEQ, HD, 128);
    map_3d(&g_maps.ctxst, ctx, SEQ, HDALL, 64); map_2d(&g_maps.ctxld, ctx, SEQ, HDALL, 128);
    map_3d(&g_maps.wo, d_in[5], HDALL, DM, 64);
    map_2d(&g_maps.h, hh, SEQ, DM, 64);
    map_2d(&g_maps.wg, d_in[7], DM, FF, 64); map_2d(&g_maps.wu, d_in[8], DM, FF, 64);
    map_2d(&g_maps.actst, act, SEQ, FF, 64); map_2d(&g_maps.actld, act, SEQ, FF, 128);
    map_3d(&g_maps.wd, d_in[9], FF, DM, 64);
    cudaFuncSetAttribute(k_mega, cudaFuncAttributeMaxDynamicSharedMemorySize, MK_SMEM);
    g_init = true;
  }
  g_ptrs.x = (const __nv_bfloat16*)d_in[0]; g_ptrs.wg = (const __nv_bfloat16*)d_in[7]; g_ptrs.wu = (const __nv_bfloat16*)d_in[8];
  g_ptrs.wo = (const __nv_bfloat16*)d_in[5]; g_ptrs.wd = (const __nv_bfloat16*)d_in[9]; g_ptrs.out = (__nv_bfloat16*)d_out;
  k_mega<<<128, 384, MK_SMEM, cudaStreamPerThread>>>(g_maps, g_ptrs);
}
```

```cpp
#include <cuda_runtime.h>
#include <cuda_bf16.h>
#include <cuda.h>
#include <stdint.h>

constexpr int SEQ = 2048, DM = 512, NH = 32, HD = 128, HDALL = 4096, FF = 1792;

__device__ __forceinline__ uint32_t smem_u32(const void* p) { return (uint32_t)__cvta_generic_to_shared(p); }
__device__ __forceinline__ void mbar_init(uint32_t bar, uint32_t count) {
  asm volatile("mbarrier.init.shared::cta.b64 [%0], %1;" :: "r"(bar), "r"(count) : "memory");
}
__device__ __forceinline__ void mbar_expect_tx(uint32_t bar, uint32_t bytes) {
  asm volatile("mbarrier.arrive.expect_tx.shared::cta.b64 _, [%0], %1;" :: "r"(bar), "r"(bytes) : "memory");
}
__device__ __forceinline__ void mbar_arrive(uint32_t bar) {
  asm volatile("mbarrier.arrive.shared::cta.b64 _, [%0];" :: "r"(bar) : "memory");
}

#define SPIN_LIMIT "2000000"
#define SPIN_DBG(IDOP, VALOP)
template<int ID> __device__ __forceinline__ void mbar_wait(uint32_t bar, uint32_t parity) {
  asm volatile("{\n.reg .pred p;\n.reg .u32 c;\nmov.u32 c, 0;\n"
    "LAB_WAIT:\n"
    "mbarrier.try_wait.parity.shared::cta.b64 p, [%0], %1;\n"
    "@p bra LAB_DONE;\n"
    "add.u32 c, c, 1;\n"
    SPIN_DBG("%2", "%1")
    "setp.gt.u32 p, c, " SPIN_LIMIT ";\n"
    "@p trap;\n"
    "bra LAB_WAIT;\n"
    "LAB_DONE:\n}" :: "r"(bar), "r"(parity), "n"(ID) : "memory");
}
template<int ID> __device__ __forceinline__ void mbar_spin(uint32_t bar, uint32_t parity) {
  asm volatile("{\n.reg .pred p;\n.reg .u32 c;\nmov.u32 c, 0;\n"
    "LAB_WAIT:\n"
    "mbarrier.test_wait.parity.shared::cta.b64 p, [%0], %1;\n"
    "@p bra LAB_DONE;\n"
    "add.u32 c, c, 1;\n"
    "setp.gt.u32 p, c, 40000000;\n"
    "@p trap;\n"
    "bra LAB_WAIT;\n"
    "LAB_DONE:\n}" :: "r"(bar), "r"(parity), "n"(ID) : "memory");
}
__device__ __forceinline__ void tma_load_2d(uint32_t dst, const CUtensorMap* m, uint32_t bar, int c0, int c1) {
  asm volatile("cp.async.bulk.tensor.2d.shared::cluster.global.mbarrier::complete_tx::bytes [%0], [%1, {%3, %4}], [%2];"
    :: "r"(dst), "l"(m), "r"(bar), "r"(c0), "r"(c1) : "memory");
}
__device__ __forceinline__ void tma_load_3d(uint32_t dst, const CUtensorMap* m, uint32_t bar, int c0, int c1, int c2) {
  asm volatile("cp.async.bulk.tensor.3d.shared::cluster.global.mbarrier::complete_tx::bytes [%0], [%1, {%3, %4, %5}], [%2];"
    :: "r"(dst), "l"(m), "r"(bar), "r"(c0), "r"(c1), "r"(c2) : "memory");
}
__device__ __forceinline__ void tma_load_5d(uint32_t dst, const CUtensorMap* m, uint32_t bar, int c0, int c1, int c2, int c3, int c4) {
  asm volatile("cp.async.bulk.tensor.5d.shared::cluster.global.mbarrier::complete_tx::bytes [%0], [%1, {%3, %4, %5, %6, %7}], [%2];"
    :: "r"(dst), "l"(m), "r"(bar), "r"(c0), "r"(c1), "r"(c2), "r"(c3), "r"(c4) : "memory");
}
__device__ __forceinline__ void prefetch_tmap(const CUtensorMap* m) {
  asm volatile("prefetch.tensormap [%0];" :: "l"(m) : "memory");
}
__device__ __forceinline__ void wgmma_fence() { asm volatile("wgmma.fence.sync.aligned;" ::: "memory"); }
__device__ __forceinline__ void wgmma_commit() { asm volatile("wgmma.commit_group.sync.aligned;" ::: "memory"); }
template<int N> __device__ __forceinline__ void wgmma_wait() { asm volatile("wgmma.wait_group.sync.aligned %0;" :: "n"(N) : "memory"); }
template<int R> __device__ __forceinline__ void reg_alloc() { asm volatile("setmaxnreg.inc.sync.aligned.u32 %0;" :: "n"(R)); }
template<int R> __device__ __forceinline__ void reg_dealloc() { asm volatile("setmaxnreg.dec.sync.aligned.u32 %0;" :: "n"(R)); }
__device__ __forceinline__ void named_bar_sync(int id, int n) { asm volatile("bar.sync %0, %1;" :: "r"(id), "r"(n) : "memory"); }
__device__ __forceinline__ void named_bar_arrive(int id, int n) { asm volatile("bar.arrive %0, %1;" :: "r"(id), "r"(n) : "memory"); }
__device__ __forceinline__ uint64_t make_desc(uint32_t addr, uint32_t lbo_bytes, uint32_t sbo_bytes) {
  uint64_t d = 0;
  d |= (uint64_t)((addr & 0x3FFFF) >> 4);
  d |= (uint64_t)(lbo_bytes >> 4) << 16;
  d |= (uint64_t)(sbo_bytes >> 4) << 32;
  d |= (uint64_t)1 << 62;
  return d;
}
__device__ __forceinline__ uint32_t desc_lo(uint32_t addr, uint32_t lbo_bytes) { return ((addr & 0x3FFFF) >> 4) + ((lbo_bytes >> 4) << 16); }
template<int N> __device__ __forceinline__ void fence_regs(float (&d)[N]) {
#pragma unroll
  for (int i = 0; i < N; i++) asm volatile("" : "+f"(d[i]) :: "memory");
}
template<int N> __device__ __forceinline__ void fence_regs(uint32_t (&d)[N]) {
#pragma unroll
  for (int i = 0; i < N; i++) asm volatile("" : "+r"(d[i]) :: "memory");
}
__device__ __forceinline__ uint32_t pack_bf16(float lo, float hi) {
  uint32_t r; asm("cvt.rn.bf16x2.f32 %0, %1, %2;" : "=r"(r) : "f"(hi), "f"(lo)); return r;
}
__device__ __forceinline__ float ex2(float x) { float y; asm("ex2.approx.ftz.f32 %0, %1;" : "=f"(y) : "f"(x)); return y; }
__device__ __forceinline__ float tanh_approx(float x) { float y; asm("tanh.approx.f32 %0, %1;" : "=f"(y) : "f"(x)); return y; }
__device__ __forceinline__ float bf16lo(uint32_t v) { return __uint_as_float(v << 16); }
__device__ __forceinline__ float bf16hi(uint32_t v) { return __uint_as_float(v & 0xffff0000u); }

__device__ __forceinline__ uint32_t mapa(uint32_t addr, uint32_t cta) {
  uint32_t r; asm("mapa.shared::cluster.u32 %0, %1, %2;" : "=r"(r) : "r"(addr), "r"(cta)); return r;
}
__device__ __forceinline__ void mbar_arrive_cl(uint32_t cluster_addr) {
  asm volatile("mbarrier.arrive.shared::cluster.b64 _, [%0];" :: "r"(cluster_addr) : "memory");
}
template<int ID> __device__ __forceinline__ void mbar_wait_cl(uint32_t bar, uint32_t parity) {
  asm volatile("{\n.reg .pred p;\n.reg .u32 c;\nmov.u32 c, 0;\n"
    "LAB_WAIT:\n"
    "mbarrier.try_wait.parity.acquire.cluster.shared::cta.b64 p, [%0], %1;\n"
    "@p bra LAB_DONE;\n"
    "add.u32 c, c, 1;\n"
    SPIN_DBG("%2", "%1")
    "setp.gt.u32 p, c, " SPIN_LIMIT ";\n"
    "@p trap;\n"
    "bra LAB_WAIT;\n"
    "LAB_DONE:\n}" :: "r"(bar), "r"(parity), "n"(ID) : "memory");
}
__device__ __forceinline__ void tma_load_2d_mc(uint32_t dst, const CUtensorMap* m, uint32_t bar, int c0, int c1) {
  asm volatile("cp.async.bulk.tensor.2d.shared::cluster.global.mbarrier::complete_tx::bytes.multicast::cluster [%0], [%1, {%3, %4}], [%2], %5;"
    :: "r"(dst), "l"(m), "r"(bar), "r"(c0), "r"(c1), "h"((uint16_t)3) : "memory");
}
__device__ __forceinline__ void tma_load_3d_mc(uint32_t dst, const CUtensorMap* m, uint32_t bar, int c0, int c1, int c2) {
  asm volatile("cp.async.bulk.tensor.3d.shared::cluster.global.mbarrier::complete_tx::bytes.multicast::cluster [%0], [%1, {%3, %4, %5}], [%2], %6;"
    :: "r"(dst), "l"(m), "r"(bar), "r"(c0), "r"(c1), "r"(c2), "h"((uint16_t)3) : "memory");
}
__device__ __forceinline__ void tma_store_2d(const CUtensorMap* m, uint32_t src, int c0, int c1) {
  asm volatile("cp.async.bulk.tensor.2d.global.shared::cta.bulk_group [%0, {%2, %3}], [%1];" :: "l"(m), "r"(src), "r"(c0), "r"(c1) : "memory");
}
__device__ __forceinline__ void tma_store_3d(const CUtensorMap* m, uint32_t src, int c0, int c1, int c2) {
  asm volatile("cp.async.bulk.tensor.3d.global.shared::cta.bulk_group [%0, {%2, %3, %4}], [%1];" :: "l"(m), "r"(src), "r"(c0), "r"(c1), "r"(c2) : "memory");
}
__device__ __forceinline__ void bulk_store(void* gdst, uint32_t src, uint32_t bytes) {
  asm volatile("cp.async.bulk.global.shared::cta.bulk_group [%0], [%1], %2;" :: "l"(gdst), "r"(src), "r"(bytes) : "memory");
}
__device__ __forceinline__ void bulk_load(uint32_t dst, const void* gsrc, uint32_t bytes, uint32_t bar) {
  asm volatile("cp.async.bulk.shared::cluster.global.mbarrier::complete_tx::bytes [%0], [%1], %2, [%3];" :: "r"(dst), "l"(gsrc), "r"(bytes), "r"(bar) : "memory");
}
__device__ __forceinline__ void prefetch_3d(const CUtensorMap* m, int c0, int c1, int c2) {
  asm volatile("cp.async.bulk.prefetch.tensor.3d.L2.global [%0, {%1, %2, %3}];" :: "l"(m), "r"(c0), "r"(c1), "r"(c2) : "memory");
}
__device__ __forceinline__ void prefetch_2d(const CUtensorMap* m, int c0, int c1) {
  asm volatile("cp.async.bulk.prefetch.tensor.2d.L2.global [%0, {%1, %2}];" :: "l"(m), "r"(c0), "r"(c1) : "memory");
}
__device__ __forceinline__ void bulk_commit() { asm volatile("cp.async.bulk.commit_group;" ::: "memory"); }
__device__ __forceinline__ void bulk_wait_read() { asm volatile("cp.async.bulk.wait_group.read 0;" ::: "memory"); }
__device__ __forceinline__ void bulk_wait_all() { asm volatile("cp.async.bulk.wait_group 0;" ::: "memory"); }
__device__ __forceinline__ void fence_async_smem() { asm volatile("fence.proxy.async.shared::cta;" ::: "memory"); }
__device__ __forceinline__ void stmatrix_x4(uint32_t addr, uint32_t a, uint32_t b, uint32_t c, uint32_t d) {
  asm volatile("stmatrix.sync.aligned.m8n8.x4.shared.b16 [%0], {%1, %2, %3, %4};" :: "r"(addr), "r"(a), "r"(b), "r"(c), "r"(d) : "memory");
}
__device__ __forceinline__ void st_async_v4(uint32_t raddr, float a, float b, float c, float d, uint32_t rbar) {
  asm volatile("st.async.weak.shared::cluster.mbarrier::complete_tx::bytes.v4.f32 [%0], {%1, %2, %3, %4}, [%5];"
    :: "r"(raddr), "f"(a), "f"(b), "f"(c), "f"(d), "r"(rbar) : "memory");
}
__device__ __forceinline__ float4 lds_v4(uint32_t addr) {
  float4 v; asm volatile("ld.shared.v4.f32 {%0, %1, %2, %3}, [%4];" : "=f"(v.x), "=f"(v.y), "=f"(v.z), "=f"(v.w) : "r"(addr) : "memory"); return v;
}
__device__ __forceinline__ float2 lds_v2(uint32_t addr) {
  float2 v; asm volatile("ld.shared.v2.f32 {%0, %1}, [%2];" : "=f"(v.x), "=f"(v.y) : "r"(addr) : "memory"); return v;
}
__device__ __forceinline__ void sts_v2(uint32_t addr, float a, float b) {
  asm volatile("st.shared.v2.f32 [%0], {%1, %2};" :: "r"(addr), "f"(a), "f"(b) : "memory");
}
__device__ __forceinline__ void flag_arrive(uint32_t* p) {
  asm volatile("red.release.gpu.global.add.u32 [%0], 1;" :: "l"(p) : "memory");
}
__device__ __forceinline__ void flag_arrive_relaxed(uint32_t* p) {
  asm volatile("red.relaxed.gpu.global.add.u32 [%0], 1;" :: "l"(p) : "memory");
}
template<int ID> __device__ __forceinline__ void flag_wait_relaxed(const uint32_t* p, uint32_t target) {
  asm volatile("{\n.reg .pred p;\n.reg .u32 c, v;\nmov.u32 c, 0;\n"
    "LAB_WAIT:\n"
    "ld.relaxed.gpu.global.u32 v, [%0];\n"
    "sub.u32 v, v, %1;\n"
    "setp.ge.s32 p, v, 0;\n"
    "@p bra LAB_DONE;\n"
    "add.u32 c, c, 1;\n"
    SPIN_DBG("%2", "v")
    "setp.gt.u32 p, c, " SPIN_LIMIT ";\n"
    "@p trap;\n"
    "bra LAB_WAIT;\n"
    "LAB_DONE:\n}" :: "l"(p), "r"(target), "n"(ID) : "memory");
}
template<int ID> __device__ __forceinline__ void flag_wait(const uint32_t* p, uint32_t target) {
  asm volatile("{\n.reg .pred p;\n.reg .u32 c, v;\nmov.u32 c, 0;\n"
    "LAB_WAIT:\n"
    "ld.acquire.gpu.global.u32 v, [%0];\n"
    "sub.u32 v, v, %1;\n"
    "setp.ge.s32 p, v, 0;\n"
    "@p bra LAB_DONE;\n"
    "add.u32 c, c, 1;\n"
    SPIN_DBG("%2", "v")
    "setp.gt.u32 p, c, " SPIN_LIMIT ";\n"
    "@p trap;\n"
    "bra LAB_WAIT;\n"
    "LAB_DONE:\n"
    "fence.proxy.async.global;\n}"
    :: "l"(p), "r"(target), "n"(ID) : "memory");
}
__device__ __forceinline__ bool flag_test(const uint32_t* p, uint32_t target) {
  uint32_t v; asm volatile("ld.acquire.gpu.global.u32 %0, [%1];" : "=r"(v) : "l"(p) : "memory");
  return (int32_t)(v - target) >= 0;
}
__device__ __forceinline__ bool mbar_test(uint32_t bar, uint32_t parity) {
  uint32_t r;
  asm volatile("{\n.reg .pred p;\nmbarrier.test_wait.parity.shared::cta.b64 p, [%1], %2;\nselp.u32 %0, 1, 0, p;\n}" : "=r"(r) : "r"(bar), "r"(parity) : "memory");
  return r != 0;
}
__device__ __forceinline__ void fence_async_global() { asm volatile("fence.proxy.async.global;" ::: "memory"); }
__device__ __forceinline__ void mbar_expect_only(uint32_t bar, uint32_t bytes) {
  asm volatile("mbarrier.expect_tx.relaxed.cta.shared::cta.b64 [%0], %1;" :: "r"(bar), "r"(bytes) : "memory");
}
__device__ __forceinline__ void prefetch_l2(const void* p, uint32_t bytes) {
  asm volatile("cp.async.bulk.prefetch.L2.global [%0], %1;" :: "l"(p), "r"(bytes) : "memory");
}
__device__ __forceinline__ void cluster_arrive() { asm volatile("barrier.cluster.arrive.release.aligned;" ::: "memory"); }
__device__ __forceinline__ void cluster_wait() { asm volatile("barrier.cluster.wait.acquire.aligned;" ::: "memory"); }

__device__ __forceinline__ void st_relaxed_v4(void* p, uint32_t a, uint32_t b, uint32_t c, uint32_t d) {
  asm volatile("st.relaxed.gpu.global.v4.u32 [%0], {%1, %2, %3, %4};" :: "l"(p), "r"(a), "r"(b), "r"(c), "r"(d) : "memory");
}
__device__ __forceinline__ void ld_nonzero_32(uint32_t (&u)[32], const void* p) {
  asm volatile("{\n.reg .pred p;\n.reg .u32 c, m;\nmov.u32 c, 0;\n"
    "LAB_WAIT:\n"
    "ld.relaxed.gpu.global.v4.u32 {%0, %1, %2, %3}, [%32+0];\n"
    "ld.relaxed.gpu.global.v4.u32 {%4, %5, %6, %7}, [%32+4096];\n"
    "ld.relaxed.gpu.global.v4.u32 {%8, %9, %10, %11}, [%32+8192];\n"
    "ld.relaxed.gpu.global.v4.u32 {%12, %13, %14, %15}, [%32+12288];\n"
    "ld.relaxed.gpu.global.v4.u32 {%16, %17, %18, %19}, [%32+16384];\n"
    "ld.relaxed.gpu.global.v4.u32 {%20, %21, %22, %23}, [%32+20480];\n"
    "ld.relaxed.gpu.global.v4.u32 {%24, %25, %26, %27}, [%32+24576];\n"
    "ld.relaxed.gpu.global.v4.u32 {%28, %29, %30, %31}, [%32+28672];\n"
    "min.u32 m, %0, %1;\n" "min.u32 m, m, %2;\n" "min.u32 m, m, %3;\n" "min.u32 m, m, %4;\n" "min.u32 m, m, %5;\n" "min.u32 m, m, %6;\n" "min.u32 m, m, %7;\n" "min.u32 m, m, %8;\n" "min.u32 m, m, %9;\n" "min.u32 m, m, %10;\n" "min.u32 m, m, %11;\n" "min.u32 m, m, %12;\n" "min.u32 m, m, %13;\n" "min.u32 m, m, %14;\n" "min.u32 m, m, %15;\n" "min.u32 m, m, %16;\n" "min.u32 m, m, %17;\n" "min.u32 m, m, %18;\n" "min.u32 m, m, %19;\n" "min.u32 m, m, %20;\n" "min.u32 m, m, %21;\n" "min.u32 m, m, %22;\n" "min.u32 m, m, %23;\n" "min.u32 m, m, %24;\n" "min.u32 m, m, %25;\n" "min.u32 m, m, %26;\n" "min.u32 m, m, %27;\n" "min.u32 m, m, %28;\n" "min.u32 m, m, %29;\n" "min.u32 m, m, %30;\n" "min.u32 m, m, %31;\n"
    "setp.ne.u32 p, m, 0;\n"
    "@p bra LAB_DONE;\n"
    "add.u32 c, c, 1;\n"
    "setp.gt.u32 p, c, " SPIN_LIMIT ";\n"
    "@p trap;\n"
    "bra LAB_WAIT;\n"
    "LAB_DONE:\n}" : "=&r"(u[0]), "=&r"(u[1]), "=&r"(u[2]), "=&r"(u[3]), "=&r"(u[4]), "=&r"(u[5]), "=&r"(u[6]), "=&r"(u[7]), "=&r"(u[8]), "=&r"(u[9]), "=&r"(u[10]), "=&r"(u[11]), "=&r"(u[12]), "=&r"(u[13]), "=&r"(u[14]), "=&r"(u[15]), "=&r"(u[16]), "=&r"(u[17]), "=&r"(u[18]), "=&r"(u[19]), "=&r"(u[20]), "=&r"(u[21]), "=&r"(u[22]), "=&r"(u[23]), "=&r"(u[24]), "=&r"(u[25]), "=&r"(u[26]), "=&r"(u[27]), "=&r"(u[28]), "=&r"(u[29]), "=&r"(u[30]), "=&r"(u[31]) : "l"(p) : "memory");
}
__device__ __forceinline__ void poll_v4(const void* p) {
  asm volatile("{\n.reg .pred p;\n.reg .u32 c, v;\nmov.u32 c, 0;\n"
    "LAB_WAIT:\n"
    "ld.relaxed.gpu.global.u32 v, [%0+12];\n"
    "setp.ne.u32 p, v, 0;\n"
    "@p bra LAB_DONE;\n"
    "add.u32 c, c, 1;\n"
    "setp.gt.u32 p, c, " SPIN_LIMIT ";\n"
    "@p trap;\n"
    "bra LAB_WAIT;\n"
    "LAB_DONE:\n}" :: "l"(p) : "memory");
}
__device__ __forceinline__ float2 ld_cg_f2(const void* p) {
  float2 v; asm volatile("ld.global.cg.v2.f32 {%0, %1}, [%2];" : "=f"(v.x), "=f"(v.y) : "l"(p) : "memory"); return v;
}
__device__ __forceinline__ uint32_t ld_cg_u32(const void* p) {
  uint32_t v; asm volatile("ld.global.cg.u32 %0, [%1];" : "=r"(v) : "l"(p) : "memory"); return v;
}
__device__ __forceinline__ uint64_t pol_first() { uint64_t p; asm("createpolicy.fractional.L2::evict_first.b64 %0, 1.0;" : "=l"(p)); return p; }
__device__ __forceinline__ uint64_t pol_normal() { uint64_t p; asm("createpolicy.fractional.L2::evict_normal.b64 %0, 1.0;" : "=l"(p)); return p; }
__device__ __forceinline__ void tma_load_2d_h(uint32_t dst, const CUtensorMap* m, uint32_t bar, int c0, int c1, uint64_t pol) {
  asm volatile("cp.async.bulk.tensor.2d.shared::cluster.global.mbarrier::complete_tx::bytes.L2::cache_hint [%0], [%1, {%3, %4}], [%2], %5;"
    :: "r"(dst), "l"(m), "r"(bar), "r"(c0), "r"(c1), "l"(pol) : "memory");
}
__device__ __forceinline__ void tma_load_3d_h(uint32_t dst, const CUtensorMap* m, uint32_t bar, int c0, int c1, int c2, uint64_t pol) {
  asm volatile("cp.async.bulk.tensor.3d.shared::cluster.global.mbarrier::complete_tx::bytes.L2::cache_hint [%0], [%1, {%3, %4, %5}], [%2], %6;"
    :: "r"(dst), "l"(m), "r"(bar), "r"(c0), "r"(c1), "r"(c2), "l"(pol) : "memory");
}
__device__ __forceinline__ void tma_load_3d_mc_h(uint32_t dst, const CUtensorMap* m, uint32_t bar, int c0, int c1, int c2, uint64_t pol) {
  asm volatile("cp.async.bulk.tensor.3d.shared::cluster.global.mbarrier::complete_tx::bytes.multicast::cluster.L2::cache_hint [%0], [%1, {%3, %4, %5}], [%2], %6, %7;"
    :: "r"(dst), "l"(m), "r"(bar), "r"(c0), "r"(c1), "r"(c2), "h"((uint16_t)3), "l"(pol) : "memory");
}
__device__ __forceinline__ void tma_store_3d_h(const CUtensorMap* m, uint32_t src, int c0, int c1, int c2, uint64_t pol) {
  asm volatile("cp.async.bulk.tensor.3d.global.shared::cta.bulk_group.L2::cache_hint [%0, {%2, %3, %4}], [%1], %5;" :: "l"(m), "r"(src), "r"(c0), "r"(c1), "r"(c2), "l"(pol) : "memory");
}
__device__ __forceinline__ uint4 ldg_v4_h(const void* p, uint64_t pol) {
  uint4 v; asm volatile("ld.global.nc.L2::cache_hint.v4.u32 {%0, %1, %2, %3}, [%4], %5;" : "=r"(v.x), "=r"(v.y), "=r"(v.z), "=r"(v.w) : "l"(p), "l"(pol)); return v;
}
__device__ __forceinline__ uint32_t ldg_h(const void* p, uint64_t pol) {
  uint32_t v; asm("ld.global.nc.L2::cache_hint.u32 %0, [%1], %2;" : "=r"(v) : "l"(p), "l"(pol)); return v;
}
__device__ __forceinline__ void ld2(bool ef, uint64_t pol, uint32_t dst, const CUtensorMap* m, uint32_t bar, int c0, int c1) {
  if (ef) tma_load_2d_h(dst, m, bar, c0, c1, pol); else tma_load_2d(dst, m, bar, c0, c1);
}
__device__ __forceinline__ void ld3(bool ef, uint64_t pol, uint32_t dst, const CUtensorMap* m, uint32_t bar, int c0, int c1, int c2) {
  if (ef) tma_load_3d_h(dst, m, bar, c0, c1, c2, pol); else tma_load_3d(dst, m, bar, c0, c1, c2);
}
__device__ __forceinline__ void ld3mc(bool ef, uint64_t pol, uint32_t dst, const CUtensorMap* m, uint32_t bar, int c0, int c1, int c2) {
  if (ef) tma_load_3d_mc_h(dst, m, bar, c0, c1, c2, pol); else tma_load_3d_mc(dst, m, bar, c0, c1, c2);
}
__device__ __forceinline__ uint64_t pol_unch() { uint64_t p; asm("createpolicy.fractional.L2::evict_unchanged.b64 %0, 1.0;" : "=l"(p)); return p; }
#define EVN 0
#define EVU 0
#define ALIAS 1
#define PUB 1
#define PUBM 31
#define EVF 91

#define PROF_T(k, i)
#define PROF_G(k, i)
#define PROF_0(i)
#define PROF_INIT()
#define PROF_DUMP()
template<int TB> __device__ __forceinline__ void wgmma_m64n128k16_ss(float (&d)[64], uint32_t da, uint32_t db, int scale_d) {
  asm volatile("{\n.reg .pred p;\n.reg .b64 da, db;\nsetp.ne.b32 p, %66, 0;\nmov.b64 da, {%64, 0x40000040};\nmov.b64 db, {%65, 0x40000040};\n"
    "wgmma.mma_async.sync.aligned.m64n128k16.f32.bf16.bf16 "
    "{%0, %1, %2, %3, %4, %5, %6, %7, %8, %9, %10, %11, %12, %13, %14, %15, "
    "%16, %17, %18, %19, %20, %21, %22, %23, %24, %25, %26, %27, %28, %29, %30, %31, "
    "%32, %33, %34, %35, %36, %37, %38, %39, %40, %41, %42, %43, %44, %45, %46, %47, "
    "%48, %49, %50, %51, %52, %53, %54, %55, %56, %57, %58, %59, %60, %61, %62, %63}, "
    "da, db, p, 1, 1, 0, %67;\n}\n"
    : "+f"(d[0]), "+f"(d[1]), "+f"(d[2]), "+f"(d[3]), "+f"(d[4]), "+f"(d[5]), "+f"(d[6]), "+f"(d[7]), "+f"(d[8]), "+f"(d[9]), "+f"(d[10]), "+f"(d[11]), "+f"(d[12]), "+f"(d[13]), "+f"(d[14]), "+f"(d[15]), "+f"(d[16]), "+f"(d[17]), "+f"(d[18]), "+f"(d[19]), "+f"(d[20]), "+f"(d[21]), "+f"(d[22]), "+f"(d[23]), "+f"(d[24]), "+f"(d[25]), "+f"(d[26]), "+f"(d[27]), "+f"(d[28]), "+f"(d[29]), "+f"(d[30]), "+f"(d[31]), "+f"(d[32]), "+f"(d[33]), "+f"(d[34]), "+f"(d[35]), "+f"(d[36]), "+f"(d[37]), "+f"(d[38]), "+f"(d[39]), "+f"(d[40]), "+f"(d[41]), "+f"(d[42]), "+f"(d[43]), "+f"(d[44]), "+f"(d[45]), "+f"(d[46]), "+f"(d[47]), "+f"(d[48]), "+f"(d[49]), "+f"(d[50]), "+f"(d[51]), "+f"(d[52]), "+f"(d[53]), "+f"(d[54]), "+f"(d[55]), "+f"(d[56]), "+f"(d[57]), "+f"(d[58]), "+f"(d[59]), "+f"(d[60]), "+f"(d[61]), "+f"(d[62]), "+f"(d[63])
    : "r"(da), "r"(db), "r"(scale_d), "n"(TB));
}
template<int TB> __device__ __forceinline__ void wgmma_m64n128k16_rs(float (&d)[64], uint32_t a0, uint32_t a1, uint32_t a2, uint32_t a3, uint32_t db, int scale_d) {
  asm volatile("{\n.reg .pred p;\n.reg .b64 db;\nsetp.ne.b32 p, %69, 0;\nmov.b64 db, {%68, 0x40000040};\n"
    "wgmma.mma_async.sync.aligned.m64n128k16.f32.bf16.bf16 "
    "{%0, %1, %2, %3, %4, %5, %6, %7, %8, %9, %10, %11, %12, %13, %14, %15, "
    "%16, %17, %18, %19, %20, %21, %22, %23, %24, %25, %26, %27, %28, %29, %30, %31, "
    "%32, %33, %34, %35, %36, %37, %38, %39, %40, %41, %42, %43, %44, %45, %46, %47, "
    "%48, %49, %50, %51, %52, %53, %54, %55, %56, %57, %58, %59, %60, %61, %62, %63}, "
    "{%64, %65, %66, %67}, db, p, 1, 1, %70;\n}\n"
    : "+f"(d[0]), "+f"(d[1]), "+f"(d[2]), "+f"(d[3]), "+f"(d[4]), "+f"(d[5]), "+f"(d[6]), "+f"(d[7]), "+f"(d[8]), "+f"(d[9]), "+f"(d[10]), "+f"(d[11]), "+f"(d[12]), "+f"(d[13]), "+f"(d[14]), "+f"(d[15]), "+f"(d[16]), "+f"(d[17]), "+f"(d[18]), "+f"(d[19]), "+f"(d[20]), "+f"(d[21]), "+f"(d[22]), "+f"(d[23]), "+f"(d[24]), "+f"(d[25]), "+f"(d[26]), "+f"(d[27]), "+f"(d[28]), "+f"(d[29]), "+f"(d[30]), "+f"(d[31]), "+f"(d[32]), "+f"(d[33]), "+f"(d[34]), "+f"(d[35]), "+f"(d[36]), "+f"(d[37]), "+f"(d[38]), "+f"(d[39]), "+f"(d[40]), "+f"(d[41]), "+f"(d[42]), "+f"(d[43]), "+f"(d[44]), "+f"(d[45]), "+f"(d[46]), "+f"(d[47]), "+f"(d[48]), "+f"(d[49]), "+f"(d[50]), "+f"(d[51]), "+f"(d[52]), "+f"(d[53]), "+f"(d[54]), "+f"(d[55]), "+f"(d[56]), "+f"(d[57]), "+f"(d[58]), "+f"(d[59]), "+f"(d[60]), "+f"(d[61]), "+f"(d[62]), "+f"(d[63])
    : "r"(a0), "r"(a1), "r"(a2), "r"(a3), "r"(db), "r"(scale_d), "n"(TB));
}
template<int TB> __device__ __forceinline__ void wgmma_m64n256k16_ss(float (&d)[128], uint32_t da, uint32_t db, int scale_d) {
  asm volatile("{\n.reg .pred p;\n.reg .b64 da, db;\nsetp.ne.b32 p, %130, 0;\nmov.b64 da, {%128, 0x40000040};\nmov.b64 db, {%129, 0x40000040};\n"
    "wgmma.mma_async.sync.aligned.m64n256k16.f32.bf16.bf16 "
    "{%0, %1, %2, %3, %4, %5, %6, %7, %8, %9, %10, %11, %12, %13, %14, %15, "
    "%16, %17, %18, %19, %20, %21, %22, %23, %24, %25, %26, %27, %28, %29, %30, %31, "
    "%32, %33, %34, %35, %36, %37, %38, %39, %40, %41, %42, %43, %44, %45, %46, %47, "
    "%48, %49, %50, %51, %52, %53, %54, %55, %56, %57, %58, %59, %60, %61, %62, %63, "
    "%64, %65, %66, %67, %68, %69, %70, %71, %72, %73, %74, %75, %76, %77, %78, %79, "
    "%80, %81, %82, %83, %84, %85, %86, %87, %88, %89, %90, %91, %92, %93, %94, %95, "
    "%96, %97, %98, %99, %100, %101, %102, %103, %104, %105, %106, %107, %108, %109, %110, %111, "
    "%112, %113, %114, %115, %116, %117, %118, %119, %120, %121, %122, %123, %124, %125, %126, %127}, "
    "da, db, p, 1, 1, 0, %131;\n}\n"
    : "+f"(d[0]), "+f"(d[1]), "+f"(d[2]), "+f"(d[3]), "+f"(d[4]), "+f"(d[5]), "+f"(d[6]), "+f"(d[7]), "+f"(d[8]), "+f"(d[9]), "+f"(d[10]), "+f"(d[11]), "+f"(d[12]), "+f"(d[13]), "+f"(d[14]), "+f"(d[15]), "+f"(d[16]), "+f"(d[17]), "+f"(d[18]), "+f"(d[19]), "+f"(d[20]), "+f"(d[21]), "+f"(d[22]), "+f"(d[23]), "+f"(d[24]), "+f"(d[25]), "+f"(d[26]), "+f"(d[27]), "+f"(d[28]), "+f"(d[29]), "+f"(d[30]), "+f"(d[31]), "+f"(d[32]), "+f"(d[33]), "+f"(d[34]), "+f"(d[35]), "+f"(d[36]), "+f"(d[37]), "+f"(d[38]), "+f"(d[39]), "+f"(d[40]), "+f"(d[41]), "+f"(d[42]), "+f"(d[43]), "+f"(d[44]), "+f"(d[45]), "+f"(d[46]), "+f"(d[47]), "+f"(d[48]), "+f"(d[49]), "+f"(d[50]), "+f"(d[51]), "+f"(d[52]), "+f"(d[53]), "+f"(d[54]), "+f"(d[55]), "+f"(d[56]), "+f"(d[57]), "+f"(d[58]), "+f"(d[59]), "+f"(d[60]), "+f"(d[61]), "+f"(d[62]), "+f"(d[63]), "+f"(d[64]), "+f"(d[65]), "+f"(d[66]), "+f"(d[67]), "+f"(d[68]), "+f"(d[69]), "+f"(d[70]), "+f"(d[71]), "+f"(d[72]), "+f"(d[73]), "+f"(d[74]), "+f"(d[75]), "+f"(d[76]), "+f"(d[77]), "+f"(d[78]), "+f"(d[79]), "+f"(d[80]), "+f"(d[81]), "+f"(d[82]), "+f"(d[83]), "+f"(d[84]), "+f"(d[85]), "+f"(d[86]), "+f"(d[87]), "+f"(d[88]), "+f"(d[89]), "+f"(d[90]), "+f"(d[91]), "+f"(d[92]), "+f"(d[93]), "+f"(d[94]), "+f"(d[95]), "+f"(d[96]), "+f"(d[97]), "+f"(d[98]), "+f"(d[99]), "+f"(d[100]), "+f"(d[101]), "+f"(d[102]), "+f"(d[103]), "+f"(d[104]), "+f"(d[105]), "+f"(d[106]), "+f"(d[107]), "+f"(d[108]), "+f"(d[109]), "+f"(d[110]), "+f"(d[111]), "+f"(d[112]), "+f"(d[113]), "+f"(d[114]), "+f"(d[115]), "+f"(d[116]), "+f"(d[117]), "+f"(d[118]), "+f"(d[119]), "+f"(d[120]), "+f"(d[121]), "+f"(d[122]), "+f"(d[123]), "+f"(d[124]), "+f"(d[125]), "+f"(d[126]), "+f"(d[127])
    : "r"(da), "r"(db), "r"(scale_d), "n"(TB));
}
template<int TB> __device__ __forceinline__ void wgmma_m64n96k16_ss(float (&d)[48], uint32_t da, uint32_t db, int scale_d) {
  asm volatile("{\n.reg .pred p;\n.reg .b64 da, db;\nsetp.ne.b32 p, %50, 0;\nmov.b64 da, {%48, 0x40000040};\nmov.b64 db, {%49, 0x40000040};\n"
    "wgmma.mma_async.sync.aligned.m64n96k16.f32.bf16.bf16 "
    "{%0, %1, %2, %3, %4, %5, %6, %7, %8, %9, %10, %11, %12, %13, %14, %15, "
    "%16, %17, %18, %19, %20, %21, %22, %23, %24, %25, %26, %27, %28, %29, %30, %31, "
    "%32, %33, %34, %35, %36, %37, %38, %39, %40, %41, %42, %43, %44, %45, %46, %47}, "
    "da, db, p, 1, 1, 0, %51;\n}\n"
    : "+f"(d[0]), "+f"(d[1]), "+f"(d[2]), "+f"(d[3]), "+f"(d[4]), "+f"(d[5]), "+f"(d[6]), "+f"(d[7]), "+f"(d[8]), "+f"(d[9]), "+f"(d[10]), "+f"(d[11]), "+f"(d[12]), "+f"(d[13]), "+f"(d[14]), "+f"(d[15]), "+f"(d[16]), "+f"(d[17]), "+f"(d[18]), "+f"(d[19]), "+f"(d[20]), "+f"(d[21]), "+f"(d[22]), "+f"(d[23]), "+f"(d[24]), "+f"(d[25]), "+f"(d[26]), "+f"(d[27]), "+f"(d[28]), "+f"(d[29]), "+f"(d[30]), "+f"(d[31]), "+f"(d[32]), "+f"(d[33]), "+f"(d[34]), "+f"(d[35]), "+f"(d[36]), "+f"(d[37]), "+f"(d[38]), "+f"(d[39]), "+f"(d[40]), "+f"(d[41]), "+f"(d[42]), "+f"(d[43]), "+f"(d[44]), "+f"(d[45]), "+f"(d[46]), "+f"(d[47])
    : "r"(da), "r"(db), "r"(scale_d), "n"(TB));
}
template<int TB> __device__ __forceinline__ void wgmma_m64n192k16_ss64(float (&d)[96], uint32_t da, uint32_t db, int scale_d) {
  asm volatile("{\n.reg .pred p;\n.reg .b64 da, db;\nsetp.ne.b32 p, %98, 0;\nmov.b64 da, {%96, 0x40000040};\nmov.b64 db, {%97, 0x80000020};\n"
    "wgmma.mma_async.sync.aligned.m64n192k16.f32.bf16.bf16 "
    "{%0, %1, %2, %3, %4, %5, %6, %7, %8, %9, %10, %11, %12, %13, %14, %15, %16, %17, %18, %19, %20, %21, %22, %23, %24, %25, %26, %27, %28, %29, %30, %31, %32, %33, %34, %35, %36, %37, %38, %39, %40, %41, %42, %43, %44, %45, %46, %47, %48, %49, %50, %51, %52, %53, %54, %55, %56, %57, %58, %59, %60, %61, %62, %63, %64, %65, %66, %67, %68, %69, %70, %71, %72, %73, %74, %75, %76, %77, %78, %79, %80, %81, %82, %83, %84, %85, %86, %87, %88, %89, %90, %91, %92, %93, %94, %95}, "
    "da, db, p, 1, 1, 0, %99;\n}"
    : "+f"(d[0]), "+f"(d[1]), "+f"(d[2]), "+f"(d[3]), "+f"(d[4]), "+f"(d[5]), "+f"(d[6]), "+f"(d[7]), "+f"(d[8]), "+f"(d[9]), "+f"(d[10]), "+f"(d[11]), "+f"(d[12]), "+f"(d[13]), "+f"(d[14]), "+f"(d[15]), "+f"(d[16]), "+f"(d[17]), "+f"(d[18]), "+f"(d[19]), "+f"(d[20]), "+f"(d[21]), "+f"(d[22]), "+f"(d[23]), "+f"(d[24]), "+f"(d[25]), "+f"(d[26]), "+f"(d[27]), "+f"(d[28]), "+f"(d[29]), "+f"(d[30]), "+f"(d[31]), "+f"(d[32]), "+f"(d[33]), "+f"(d[34]), "+f"(d[35]), "+f"(d[36]), "+f"(d[37]), "+f"(d[38]), "+f"(d[39]), "+f"(d[40]), "+f"(d[41]), "+f"(d[42]), "+f"(d[43]), "+f"(d[44]), "+f"(d[45]), "+f"(d[46]), "+f"(d[47]), "+f"(d[48]), "+f"(d[49]), "+f"(d[50]), "+f"(d[51]), "+f"(d[52]), "+f"(d[53]), "+f"(d[54]), "+f"(d[55]), "+f"(d[56]), "+f"(d[57]), "+f"(d[58]), "+f"(d[59]), "+f"(d[60]), "+f"(d[61]), "+f"(d[62]), "+f"(d[63]), "+f"(d[64]), "+f"(d[65]), "+f"(d[66]), "+f"(d[67]), "+f"(d[68]), "+f"(d[69]), "+f"(d[70]), "+f"(d[71]), "+f"(d[72]), "+f"(d[73]), "+f"(d[74]), "+f"(d[75]), "+f"(d[76]), "+f"(d[77]), "+f"(d[78]), "+f"(d[79]), "+f"(d[80]), "+f"(d[81]), "+f"(d[82]), "+f"(d[83]), "+f"(d[84]), "+f"(d[85]), "+f"(d[86]), "+f"(d[87]), "+f"(d[88]), "+f"(d[89]), "+f"(d[90]), "+f"(d[91]), "+f"(d[92]), "+f"(d[93]), "+f"(d[94]), "+f"(d[95])
    : "r"(da), "r"(db), "r"(scale_d), "n"(TB));
}
#define FLAG_WAIT flag_wait
__device__ __align__(1024) __nv_bfloat16 g_xn[SEQ * DM];
__device__ __align__(1024) __nv_bfloat16 g_k[NH * SEQ * HD];
__device__ __align__(1024) __nv_bfloat16 g_v[NH * SEQ * HD];
__device__ __align__(1024) __nv_bfloat16 g_ctx[SEQ * HDALL];
__device__ __align__(1024) __nv_bfloat16 g_h[SEQ * DM];
__device__ __align__(1024) __nv_bfloat16 g_act[SEQ * FF];
__device__ __align__(1024) __nv_bfloat16 g_act1[SEQ * 768];
__device__ __align__(1024) float g_cs[2 * FF];
__device__ __align__(1024) float2 g_stats[16 * 8 * 128];
__device__ __align__(1024) uint32_t g_sync[320 * 8];
__device__ unsigned long long g_ticket;
constexpr int C_XN = 0, C_CS = 16, C_KV = 32, C_CTX = 160, C_H = 224, C_ACT = 240;

struct Softmax { float m0, m1, mc0, mc1, l0, l1; int th0, th1; };
constexpr float SM_C = 0.08838834764831845f * 1.4426950408889634f;
constexpr float SM_TAU = 16.f;

__device__ __forceinline__ void row_max(const float (&s)[64], float& mx0, float& mx1) {
  float a0[4], a1[4];
#pragma unroll
  for (int i = 0; i < 4; i++) { a0[i] = fmaxf(s[4 * i], s[4 * i + 1]); a1[i] = fmaxf(s[4 * i + 2], s[4 * i + 3]); }
#pragma unroll
  for (int j = 4; j < 16; j++) {
    a0[j & 3] = fmaxf(a0[j & 3], fmaxf(s[4 * j], s[4 * j + 1])); a1[j & 3] = fmaxf(a1[j & 3], fmaxf(s[4 * j + 2], s[4 * j + 3]));
  }
  mx0 = fmaxf(fmaxf(a0[0], a0[1]), fmaxf(a0[2], a0[3])); mx1 = fmaxf(fmaxf(a1[0], a1[1]), fmaxf(a1[2], a1[3]));
  mx0 = fmaxf(mx0, __shfl_xor_sync(0xffffffffu, mx0, 1)); mx1 = fmaxf(mx1, __shfl_xor_sync(0xffffffffu, mx1, 1));
  mx0 = fmaxf(mx0, __shfl_xor_sync(0xffffffffu, mx0, 2)); mx1 = fmaxf(mx1, __shfl_xor_sync(0xffffffffu, mx1, 2));
}
__device__ __forceinline__ void sm_set_ref(Softmax& st, float m0, float m1) {
  st.mc0 = m0 * SM_C; st.mc1 = m1 * SM_C;
  const float t0 = m0 + SM_TAU / SM_C, t1 = m1 + SM_TAU / SM_C;
  st.th0 = t0 >= 0.f ? __float_as_int(t0) : (int)0x80000000;
  st.th1 = t1 >= 0.f ? __float_as_int(t1) : (int)0x80000000;
}
__device__ __forceinline__ void sm_first(float (&s)[64], Softmax& st, int row_in_blk, int q) {
#pragma unroll
  for (int j = 0; j < 16; j++) {
    const int c = 8 * j + 2 * q;
    if (c > row_in_blk) s[4 * j] = -INFINITY;
    if (c + 1 > row_in_blk) s[4 * j + 1] = -INFINITY;
    if (c > row_in_blk + 8) s[4 * j + 2] = -INFINITY;
    if (c + 1 > row_in_blk + 8) s[4 * j + 3] = -INFINITY;
  }
  float mx0, mx1;
  row_max(s, mx0, mx1);
  sm_set_ref(st, mx0, mx1);
  st.m0 = mx0; st.m1 = mx1;
  st.l0 = 0.f; st.l1 = 0.f;
}
__device__ __forceinline__ bool sm_next(float (&s)[64], Softmax& st, float& al0, float& al1) {
  int a[4];
#pragma unroll
  for (int i = 0; i < 4; i++) {
    const int o = (i >> 1) * 32 + (i & 1) * 2;
    a[i] = __vimax3_s32(__float_as_int(s[o]), __float_as_int(s[o + 1]), __float_as_int(s[o + 4]));
  }
#pragma unroll
  for (int i = 0; i < 4; i++) {
    const int o = (i >> 1) * 32 + (i & 1) * 2;
    a[i] = __vimax3_s32(a[i], __float_as_int(s[o + 5]), __float_as_int(s[o + 8]));
#pragma unroll
    for (int k = 2; k < 7; k++) a[i] = __vimax3_s32(a[i], __float_as_int(s[o + 4 * k + 1]), __float_as_int(s[o + 4 * k + 4]));
  }
  const int mx0 = __vimax3_s32(a[0], a[2], max(__float_as_int(s[29]), __float_as_int(s[61])));
  const int mx1 = __vimax3_s32(a[1], a[3], max(__float_as_int(s[31]), __float_as_int(s[63])));
  const bool bad = __any_sync(0xffffffffu, mx0 >= st.th0 || mx1 >= st.th1);
  if (bad) {
    float d0, d1;
    row_max(s, d0, d1);
    d0 = fmaxf(d0, st.m0); d1 = fmaxf(d1, st.m1);
    al0 = ex2((st.m0 - d0) * SM_C); al1 = ex2((st.m1 - d1) * SM_C);
    st.m0 = d0; st.m1 = d1;
    sm_set_ref(st, d0, d1);
    st.l0 *= al0; st.l1 *= al1;
  }
  return bad;
}
template<int J0, int J1>
__device__ __forceinline__ void sm_exp(float (&s)[64], const Softmax& st) {
  const float n0 = -st.mc0, n1 = -st.mc1;
#pragma unroll
  for (int j = J0; j < J1; j++) {
    s[4 * j] = ex2(fmaf(s[4 * j], SM_C, n0)); s[4 * j + 1] = ex2(fmaf(s[4 * j + 1], SM_C, n0));
    s[4 * j + 2] = ex2(fmaf(s[4 * j + 2], SM_C, n1)); s[4 * j + 3] = ex2(fmaf(s[4 * j + 3], SM_C, n1));
  }
}
__device__ __forceinline__ void sm_sum_cvt(const float (&s)[64], uint32_t (&p)[32], Softmax& st) {
  float r0 = 0.f, r1 = 0.f, r2 = 0.f, r3 = 0.f;
#pragma unroll
  for (int j = 0; j < 16; j++) { r0 += s[4 * j]; r1 += s[4 * j + 1]; r2 += s[4 * j + 2]; r3 += s[4 * j + 3]; }
  st.l0 += r0 + r1; st.l1 += r2 + r3;
#pragma unroll
  for (int i = 0; i < 32; i++) p[i] = pack_bf16(s[2 * i], s[2 * i + 1]);
}
__device__ __forceinline__ void issue_qk(float (&s)[64], const uint32_t (&qf)[32], uint32_t ks) {
  const uint32_t db = desc_lo(ks, 16);
#pragma unroll
  for (int kk = 0; kk < 8; kk++)
    wgmma_m64n128k16_rs<0>(s, qf[4 * kk], qf[4 * kk + 1], qf[4 * kk + 2], qf[4 * kk + 3], db + (kk >> 2) * 1024 + (kk & 3) * 2, kk != 0);
}
__device__ __forceinline__ void issue_pv(float (&o)[64], const uint32_t (&p)[32], uint32_t vs, int accumulate) {
  const uint32_t db = desc_lo(vs, 16384);
#pragma unroll
  for (int kk = 0; kk < 8; kk++)
    wgmma_m64n128k16_rs<1>(o, p[4 * kk], p[4 * kk + 1], p[4 * kk + 2], p[4 * kk + 3], db + kk * 128, kk == 0 ? accumulate : 1);
}
template<int K0>
__device__ __forceinline__ void issue128(float (&d)[64], uint32_t slot, int wg, bool first) {
  const uint32_t da = desc_lo(slot + wg * 8192, 16), db = desc_lo(slot + 16384, 8192);
#pragma unroll
  for (int k = K0; k < 4; k++) wgmma_m64n128k16_ss<1>(d, da + k * 2, db + k * 128, !(first && k == K0));
}

__device__ __forceinline__ void issue128h(float (&d)[64], uint32_t slot, int wg) {
  const uint32_t da = desc_lo(slot + wg * 8192, 16), db = desc_lo(slot + 16384, 4096);
#pragma unroll
  for (int k = 0; k < 4; k++) wgmma_m64n128k16_ss<1>(d, da + k * 2, db + (k >> 1) * 512 + (k & 1) * 128, 1);
}

struct Maps { CUtensorMap ckv, wk, wv, wq, xn, kst, vst, kld, vld, ctxst, ctxld, wo, h, wg, wu, actst, actld, wd, act1st, act1ld, wd32, wq2, wg32, wu32; };
struct Ptrs { const __nv_bfloat16 *x, *wg, *wu, *wo, *wd, *ckv, *wk, *wv; __nv_bfloat16* out; };

constexpr uint32_t G_ST = 49152, S_ST = 32768;
constexpr uint32_t O_STG = 196608, O_CS = 229376, O_BAR = 231168;
constexpr uint32_t B_GF = O_BAR, B_GE = O_BAR + 32, B_SF = O_BAR + 64, B_SE = O_BAR + 112, B_TF = O_BAR + 160, B_TE = O_BAR + 176,
                   B_XR = O_BAR + 192, B_XF = O_BAR + 208, B_CS = O_BAR + 224, B_PB = O_BAR + 232;
constexpr int MK_SMEM = 232448;

__device__ __forceinline__ int attn_qblock(int h, int r, int t) {
  return t == 0 ? 15 - r : (t == 1 ? 8 + r : (((t == 2) == ((h & 1) != 0)) ? r : 7 - r));
}

__global__ void __cluster_dims__(2, 1, 1) __launch_bounds__(384, 1)
k_mega(const __grid_constant__ Maps maps, const __grid_constant__ Ptrs ptrs) {
  extern __shared__ __align__(1024) uint8_t smem_raw[];
  const uint32_t sb = smem_u32(smem_raw);
  const int wg = __shfl_sync(0xffffffffu, threadIdx.x >> 7, 0);
  const int b = blockIdx.x, h = b >> 2, r = b & 3, rho = b & 1;
  const int tm = b >> 3, tn = (b >> 1) & 3;
#define CE(i)
  CE(0);
  if (wg == 2) {
    reg_dealloc<40>();
    if (threadIdx.x == 256) {
      prefetch_3d(rho ? &maps.wv : &maps.wk, 0, 0, h * 2); prefetch_3d(rho ? &maps.wv : &maps.wk, 0, 64, h * 2);
      CE(1);
      for (int s = 0; s < 4; s++) { mbar_init(sb + B_GF + 8 * s, 1); mbar_init(sb + B_GE + 8 * s, 16); }
      for (int s = 0; s < 6; s++) { mbar_init(sb + B_SF + 8 * s, 1); mbar_init(sb + B_SE + 8 * s, 8); }
      for (int s = 0; s < 2; s++) {
        mbar_init(sb + B_TF + 8 * s, 4); mbar_init(sb + B_TE + 8 * s, 1); mbar_init(sb + B_XR + 8 * s, 1); mbar_init(sb + B_XF + 8 * s, 1);
      }
      mbar_init(sb + B_CS, 1); mbar_init(sb + B_PB, 2);
      asm volatile("fence.mbarrier_init.release.cluster;" ::: "memory");
    }
    if (threadIdx.x == 352) { prefetch_2d(&maps.ckv, 0, (12 + r) * 128); prefetch_2d(&maps.ckv, 64, (12 + r) * 128); }
    __syncwarp();
    PROF_INIT();
    named_bar_sync(0, 384);
    asm volatile("barrier.cluster.arrive.relaxed.aligned;" ::: "memory");
    cluster_wait();
    if (threadIdx.x == 256) PROF_T(1, 27);
    const int warp = (threadIdx.x >> 5) & 3, lane = threadIdx.x & 31;
    if (warp == 0) {
      if (lane == 0) {
        PROF_G(0, 16);
        unsigned long long ticket;
        asm volatile("atom.global.add.u64 %0, [%1], 1;" : "=l"(ticket) : "l"(&g_ticket) : "memory");
        asm volatile("{\n.reg .u64 t;\nadd.u64 t, %0, 1;\nsub.u64 %0, t, 1;\n}" : "+l"(ticket) :: "memory");
        const uint64_t pF = pol_first();
        const uint64_t pN = EVN ? pol_normal() : pol_unch();
#define EVX (EVN | EVU)
#pragma unroll 1
        for (int f = 0; f < 32; f++) {
          const int st = f & 3, kb = f & 7, mb = (3 - (f >> 3)) * 4 + r;
          const uint32_t bar = sb + B_GF + 8 * st, sa = sb + st * G_ST;
          mbar_wait<1>(sb + B_GE + 8 * st, ((f >> 2) & 1) ^ 1);
          mbar_expect_tx(bar, G_ST);
          if (EVX & 1) ld2(true, pN, sa, &maps.ckv, bar, kb * 64, mb * 128); else
          ld2(EVF & 1, pF, sa, &maps.ckv, bar, kb * 64, mb * 128);
          if (EVX & 2) ld3mc(true, pN, sa + 16384 + rho * 16384, rho ? &maps.wv : &maps.wk, bar, 0, kb * 64, h * 2); else
          ld3mc((EVF & 4) || ((EVF & 2) && f >= 24) || ((EVF & 2048) && f >= 16), pF, sa + 16384 + rho * 16384, rho ? &maps.wv : &maps.wk, bar, 0, kb * 64, h * 2);
          if (f == 8) {
            prefetch_3d(&maps.wq, 0, r * 128, h * 2); prefetch_3d(&maps.wq, 0, r * 128 + 64, h * 2);
          }
        }
        asm volatile("" : "+l"(ticket) :: "memory");
        const uint32_t ep1 = (uint32_t)(ticket >> 7) + 1;
        int sl = 0; uint32_t ph = 1;
        auto s_acq = [&](uint32_t bytes) -> uint32_t {
          mbar_wait<2>(sb + B_SE + 8 * sl, ph);
          mbar_expect_tx(sb + B_SF + 8 * sl, bytes);
          return sb + sl * S_ST;
        };
        auto s_nxt = [&]() { if (++sl == 6) { sl = 0; ph ^= 1; } };
        auto s_throttle = [&](int n) { const int a = sl - n; mbar_wait<13>(sb + B_SF + 8 * (a < 0 ? a + 6 : a), a < 0 ? ph : ph ^ 1); };
        auto g_drain = [&](int d, uint32_t par) {
          if (d == 0) mbar_wait<3>(sb + B_GE, par);
          if (d == 1) mbar_wait<3>(sb + B_GE + 8, par);
          if (d == 3) mbar_wait<3>(sb + B_GE + 16, par);
          if (d == 4) mbar_wait<3>(sb + B_GE + 24, par);
        };
#pragma unroll 1
        for (int t = 0; t < 4; t++) {
          const int qb = attn_qblock(h, r, t);
          flag_wait<4>(&g_sync[(C_XN + qb) * 8], ep1 * 24);
          if (t == 0) PROF_T(1, 3);
#pragma unroll 1
          for (int kb = 0; kb < 8; kb++) {
            if (t == 0) g_drain(kb, 1);
            const uint32_t d = s_acq(S_ST), bar = sb + B_SF + 8 * sl;
            const int kr = kb;
            ld2((EVX & 4) || ((EVF & 32) && (t < 2 || qb > 3 || t == 3)), (EVX & 4) ? pN : pF, d, &maps.xn, bar, kr * 64, qb * 128);
            ld3((EVX & 8) || ((EVF & 4096) && t == 3), (EVX & 8) ? pN : pF, d + 16384, &maps.wq, bar, 0, kr * 64, h * 2);
            s_nxt();
          }
#define KV_EF ((EVF & 1024) || ((EVF & 64) && (t == 3 || blk >= (t == 0 ? 12 : (t == 1 ? 8 : 4)))) || ((EVF & 8192) && t == 3) || ((EVF & 16384) && t == 0 && blk >= 12))
          auto ld_kv = [&](const CUtensorMap* mp, int blk) {
            const uint32_t d = s_acq(S_ST);
            if (KV_EF) ld3(true, pF, d, mp, sb + B_SF + 8 * sl, 0, h * SEQ + blk * 128, 0);
            else ld3(EVX & 16, pN, d, mp, sb + B_SF + 8 * sl, 0, h * SEQ + blk * 128, 0);
            s_nxt();
          };
          if (t == 0) PROF_T(1, 4);
          if (t == 0) FLAG_WAIT<5>(&g_sync[(C_KV + h * 4) * 8], ep1 * 8);
          if (t == 0) PROF_T(1, 5);
          ld_kv(&maps.kld, qb);
#pragma unroll 1
          for (int j = qb; j > 0; j--) {
            if (t == 0 && (j & 3) == 0) FLAG_WAIT<5>(&g_sync[(C_KV + h * 4 + 4 - (j >> 2)) * 8], ep1 * 8);
            ld_kv(&maps.kld, j - 1);
            ld_kv(&maps.vld, j);
          }
          ld_kv(&maps.vld, 0);
          if (t == 2) { prefetch_l2(ptrs.wo + b * 32 * DM, 32 * DM * 2); prefetch_l2(ptrs.x + b * 16 * DM, 16 * DM * 2); }
        }
        const int fg = tn * 2 + rho;
        {
          const int c1 = tm < 4 ? 1 : 0;
          int npre = 0;
#pragma unroll 1
          for (int kb = 0; kb < 32; kb++) {
            const int cls = (kb >> 4) ^ c1;
            const int k0 = (16 * rho + ((kb >> 1) & 7) * 2 + cls) * 128 + (kb & 1) * 64;
            if ((kb & 15) == 0) {
              PROF_T(1, 6 + (kb >> 4) * 2);
              const uint32_t* flag = &g_sync[(C_CTX + (tm * 2 + rho) * 2 + cls) * 8];
              int s2 = sl; uint32_t p2 = ph; bool ok = false;
#pragma unroll 1
              for (int it = 0; it < 256 && npre < 6; it++) {
                ok = flag_test(flag, ep1 * 16);
                if (ok) break;
#pragma unroll 1
                while (npre < 6 && mbar_test(sb + B_SE + 8 * s2, p2)) {
                  mbar_expect_only(sb + B_SF + 8 * s2, 16384);
                  tma_load_3d(sb + s2 * S_ST + 16384, &maps.wo, sb + B_SF + 8 * s2, 0, k0 + (npre >> 1) * 256 + (npre & 1) * 64, tn * 2);
                  npre++;
                  if (++s2 == 6) { s2 = 0; p2 ^= 1; }
                }
              }
              if (ok) fence_async_global(); else
              FLAG_WAIT<7>(flag, ep1 * 16);
              PROF_T(1, 7 + (kb >> 4) * 2);
            }
            if (kb == 8) {
              flag_wait<6>(&g_sync[C_CS * 8], ep1 * 128);
              mbar_expect_tx(sb + B_CS, 1792);
              bulk_load(sb + O_CS, g_cs + fg * 224, 896, sb + B_CS);
              bulk_load(sb + O_CS + 896, g_cs + FF + fg * 224, 896, sb + B_CS);
              prefetch_l2(ptrs.wd + b * 14 * DM, 14 * DM * 2);
            }
            const uint32_t d = sb + sl * S_ST, bar = sb + B_SF + 8 * sl;
            if (npre > 0) { mbar_expect_tx(bar, 16384); npre--; }
            else { s_acq(S_ST); tma_load_3d(d + 16384, &maps.wo, bar, 0, k0, tn * 2); }
            tma_load_2d(d, &maps.ctxld, bar, k0, tm * 128);
            s_nxt();
          }
        }
        PROF_T(1, 0);
#pragma unroll 1
        for (int f = 0; f < 16; f++) {
          const int st = f & 3, kb = f & 7, x0 = fg * 224 + (f >> 3) * 128;
          const uint32_t bar = sb + B_GF + 8 * st, sa = sb + st * G_ST;
          mbar_wait<8>(sb + B_GE + 8 * st, (f >> 2) & 1);
          if (f < 8) {
            mbar_expect_only(bar, 32768);
            tma_load_2d(sa + 16384, &maps.wg, bar, x0, kb * 64);
            tma_load_2d(sa + 24576, &maps.wg, bar, x0 + 64, kb * 64);
            tma_load_2d(sa + 32768, &maps.wu, bar, x0, kb * 64);
            tma_load_2d(sa + 40960, &maps.wu, bar, x0 + 64, kb * 64);
          } else {
            mbar_expect_only(bar, 24576);
            tma_load_3d(sa + 16384, &maps.wg32, bar, 0, kb * 64, fg * 7 + 4);
            tma_load_3d(sa + 28672, &maps.wu32, bar, 0, kb * 64, fg * 7 + 4);
          }
          if (f >= 3) {
            if (f == 3) {
              PROF_T(1, 10);
              FLAG_WAIT<9>(&g_sync[(C_H + tm) * 8], ep1 * 16);
              PROF_T(1, 11);
#pragma unroll 1
              for (int i = 0; i < 3; i++) {
                mbar_expect_tx(sb + B_GF + 8 * i, 16384);
                tma_load_2d_mc(sb + i * G_ST + rho * 8192, &maps.h, sb + B_GF + 8 * i, i * 64, tm * 128 + rho * 64);
              }
            }
            mbar_expect_tx(bar, 16384);
            tma_load_2d_mc(sa + rho * 8192, &maps.h, bar, kb * 64, tm * 128 + rho * 64);
          }
        }
        PROF_T(1, 1);
#pragma unroll 1
        for (int d = 0; d < 8; d++) {
          if (d < 6) g_drain(d, 0);
          if (d == 0) { PROF_T(1, 12); FLAG_WAIT<10>(&g_sync[(C_ACT + (tm * 2 + rho) * 2) * 8], ep1 * 8); PROF_T(1, 13); }
          const int k0 = (4 * rho + (d >> 1)) * 224 + (d & 1) * 64;
          const uint32_t dd = s_acq(S_ST), bar = sb + B_SF + 8 * sl;
          tma_load_3d(dd + 16384, &maps.wd, bar, 0, k0, tn * 2);
          tma_load_2d(dd, &maps.actld, bar, k0, tm * 128);
          s_nxt();
        }
        {
          auto ld_wd = [&](int j, int s2) {
#pragma unroll
            for (int e = 0; e < 2; e++) {
              const int u = 2 * j + e, g = (u * 11) >> 5;
              tma_load_3d(sb + s2 * S_ST + 16384 + e * 8192, &maps.wd32, sb + B_SF + 8 * s2, 0, (4 * rho + g) * 224 + 128 + (u - 3 * g) * 32, tn * 2);
            }
          };
          PROF_T(1, 14);
          const uint32_t* flag = &g_sync[(C_ACT + (tm * 2 + rho) * 2 + 1) * 8];
          int npre = 0;
          int s2 = sl; uint32_t p2 = ph; bool ok = false;
#pragma unroll 1
          for (int it = 0; it < 256 && npre < 6; it++) {
            ok = flag_test(flag, ep1 * 8);
            if (ok) break;
#pragma unroll 1
            while (npre < 6 && mbar_test(sb + B_SE + 8 * s2, p2)) {
              mbar_expect_only(sb + B_SF + 8 * s2, 16384);
              ld_wd(npre, s2);
              npre++;
              if (++s2 == 6) { s2 = 0; p2 ^= 1; }
            }
          }
          if (ok) fence_async_global(); else
          FLAG_WAIT<10>(flag, ep1 * 8);
          PROF_T(1, 15);
#pragma unroll 1
          for (int j = 0; j < 6; j++) {
            const uint32_t bar = sb + B_SF + 8 * sl;
            if (j < npre) mbar_expect_tx(bar, 16384);
            else { s_acq(S_ST); ld_wd(j, sl); }
            tma_load_2d(sb + sl * S_ST, &maps.act1ld, bar, rho * 384 + j * 64, tm * 128);
            s_nxt();
          }
        }
        PROF_T(1, 2);
      }
    } else {
#pragma unroll 1
      for (int i = warp - 1; i < 16; i += 3) {
        const int row = b * 16 + i;
        const uint4* src = reinterpret_cast<const uint4*>(ptrs.x + row * DM);

        const uint64_t pF = pol_first();
        const uint4 a = ldg_v4_h(src + lane, pF), c = ldg_v4_h(src + lane + 32, pF);
        uint32_t w[8] = {a.x, a.y, a.z, a.w, c.x, c.y, c.z, c.w};
        float s = 0.f;
#pragma unroll
        for (int k = 0; k < 8; k++) s += bf16lo(w[k]) + bf16hi(w[k]);
#pragma unroll
        for (int o = 16; o > 0; o >>= 1) s += __shfl_xor_sync(0xffffffffu, s, o);
        const float mean = s * (1.f / 512.f);
        float ss = 0.f;
#pragma unroll
        for (int k = 0; k < 8; k++) { const float u = bf16lo(w[k]) - mean, v = bf16hi(w[k]) - mean; ss += u * u + v * v; }
#pragma unroll
        for (int o = 16; o > 0; o >>= 1) ss += __shfl_xor_sync(0xffffffffu, ss, o);
        const float rstd = rsqrtf(ss * (1.f / 512.f) + 1e-5f);
#pragma unroll
        for (int k = 0; k < 8; k++) w[k] = pack_bf16((bf16lo(w[k]) - mean) * rstd, (bf16hi(w[k]) - mean) * rstd);
        uint4* dst = reinterpret_cast<uint4*>(g_xn + row * DM);
        dst[lane] = make_uint4(w[0], w[1], w[2], w[3]);
        dst[lane + 32] = make_uint4(w[4], w[5], w[6], w[7]);
      }
      __syncwarp();
      if (lane == 0) flag_arrive(&g_sync[(C_XN + (b >> 3)) * 8]);
      if (warp == 3) {
        mbar_wait<12>(sb + B_GF + 24, 0);
        mbar_wait<12>(sb + B_GF + 24, 1);
        if (lane < 28) {
          const int cp = lane % 14, hf = lane / 14;
          const uint32_t* src = reinterpret_cast<const uint32_t*>((b < 64 ? ptrs.wg : ptrs.wu) + (size_t)hf * 256 * FF + (b & 63) * 28 + cp * 2);
          float s0 = 0.f, s1 = 0.f;
          const uint64_t pF = pol_first();
#pragma unroll 8
          for (int k = 0; k < 256; k++) { const uint32_t v = ldg_h(src + k * (FF / 2), pF); s0 += bf16lo(v); s1 += bf16hi(v); }
          const float t0 = __shfl_down_sync(0x0fffffffu, s0, 14), t1 = __shfl_down_sync(0x0fffffffu, s1, 14);
          if (lane < 14) *reinterpret_cast<float2*>(g_cs + b * 28 + cp * 2) = make_float2(s0 + t0, s1 + t1);
        }
        __syncwarp();
        if (lane == 0) flag_arrive(&g_sync[C_CS * 8]);
      } else if (lane == 0) {
        const int w = warp - 1;
        const uint32_t stg = sb + O_STG + w * 16384;
        const uint32_t xr_peer = mapa(sb + B_XR + 8 * w, rho ^ 1);
#pragma unroll 1
        for (int job = 0; job < 15; job++) {
          mbar_wait<11>(sb + B_TF + 8 * w, job & 1);
          if (w == 0) PROF_T(3, job);
          uint32_t* flag = nullptr;
          if (job < 8) {
            const int i = job >> 1;
            if (EVX & 64) tma_store_3d_h((job & 1) ? &maps.vst : &maps.kst, stg, 0, h * SEQ + ((3 - i) * 4 + r) * 128 + w * 64, 0, EVN ? pol_normal() : pol_unch());
            else
            tma_store_3d((job & 1) ? &maps.vst : &maps.kst, stg, 0, h * SEQ + ((3 - i) * 4 + r) * 128 + w * 64, 0);
            if (job & 1) flag = &g_sync[(C_KV + h * 4 + i) * 8];
          } else if (job < 12) {
            const int qb = attn_qblock(h, r, job - 8);
            if (EVX & 128) tma_store_3d_h(&maps.ctxst, stg, 0, qb * 128 + w * 64, h * 2, EVN ? pol_normal() : pol_unch());
            else
            tma_store_3d(&maps.ctxst, stg, 0, qb * 128 + w * 64, h * 2);
            flag = &g_sync[(C_CTX + (qb * 2 + (h >> 4)) * 2 + (h & 1)) * 8];
          } else if (job == 12) {
            tma_store_2d(&maps.h, stg, tn * 128 + rho * 64, tm * 128 + w * 64);
            bulk_store(g_stats + (tm * 8 + tn * 2 + rho) * 128 + w * 64, stg + 8192, 512);
            flag = &g_sync[(C_H + tm) * 8];
          } else {
            const CUtensorMap* am = job == 13 ? &maps.actst : &maps.act1st;
            const int x0 = (tn * 2 + rho) * (job == 13 ? 224 : 96);
            tma_store_2d(am, stg, x0, tm * 128 + w * 64);
            tma_store_2d(am, stg + 8192, x0 + (job == 13 ? 64 : 32), tm * 128 + w * 64);
            flag = &g_sync[(C_ACT + (tm * 2 + (tn >> 1)) * 2 + (job - 13)) * 8];
          }
          bulk_commit();
          bulk_wait_read();
          if (w == 0) PROF_T(4, job);
          mbar_arrive(sb + B_TE + 8 * w);
          if (job == 11 || job == 14) mbar_arrive_cl(xr_peer);
          if (flag) {
            bulk_wait_all(); if (w == 0) PROF_T(5, job);
            const int cls = job < 8 ? 1 : (job < 12 ? 2 : (4 << (job - 12)));
            if (PUBM & cls) {
              if (PUB & 2) asm volatile("fence.proxy.async;" ::: "memory");
              if (PUB & 4) asm volatile("fence.proxy.async.global;" ::: "memory");
              if (PUB & 1) flag_arrive(flag); else flag_arrive_relaxed(flag);
            } else flag_arrive_relaxed(flag);
          }
          if (w == 0) PROF_T(2, job);
        }
      }
    }
    __syncwarp();
    PROF_DUMP();
    asm volatile("barrier.cluster.arrive.relaxed.aligned;" ::: "memory");
    asm volatile("barrier.cluster.wait.aligned;" ::: "memory");
  } else {
    reg_alloc<232>();
    const int lane = threadIdx.x & 31, warp = (threadIdx.x >> 5) & 3, q = lane & 3;
    const int row_in_blk = wg * 64 + warp * 16 + (lane >> 2);
    const uint32_t stg = sb + O_STG + wg * 16384;
    const uint32_t stm = stg + (warp * 16 + (lane & 7) + ((lane >> 3) & 1) * 8) * 128 + (((lane >> 4) ^ (lane & 7)) << 4);
    const uint32_t ge_cl = mapa(sb + B_GE, (lane & 1) ^ rho);
    auto g_release = [&](int st) { if (lane < 2) mbar_arrive_cl(ge_cl + 8 * st); };
    uint32_t jpar = 1;
    auto stg_acquire = [&]() { mbar_wait<20>(sb + B_TE + 8 * wg, jpar); jpar ^= 1; };
    auto stg_publish = [&]() { fence_async_smem(); __syncwarp(); if (lane == 0) mbar_arrive(sb + B_TF + 8 * wg); };
    auto stg_put = [&](int atom, int jp, uint32_t a, uint32_t c, uint32_t d, uint32_t e) {
      stmatrix_x4((stm + atom * 8192) ^ (((2 * jp) & 7) << 4), a, c, d, e);
    };
    CE(1);
    PROF_INIT();
    named_bar_sync(0, 384);
    asm volatile("barrier.cluster.arrive.relaxed.aligned;" ::: "memory");
    cluster_wait();
    if (threadIdx.x == 0) PROF_0(0);

    int sl = 0; uint32_t ph = 0;
    auto s_nxt = [&]() { if (++sl == 6) { sl = 0; ph ^= 1; } };
    auto s_release = [&](int a) { if (lane == 0) mbar_arrive(sb + B_SE + 8 * a); };
    float s[64];
    uint32_t qf[32];
    {
      float acc[128];
      uint32_t pk[64];
      auto put_tile = [&](int half) {
        stg_acquire();
#pragma unroll
        for (int jp = 0; jp < 8; jp++)
          stg_put(jp >> 2, jp, pk[half * 32 + 4 * jp], pk[half * 32 + 4 * jp + 1], pk[half * 32 + 4 * jp + 2], pk[half * 32 + 4 * jp + 3]);
        stg_publish();
      };
#pragma unroll
      for (int i = 0; i < 64; i++) pk[i] = 0;
      for (int i = 0; i < 4; i++) {
#pragma unroll
        for (int kb = 0; kb < 8; kb++) {
          const int st = kb & 3;
          mbar_wait<21>(sb + B_GF + 8 * st, (kb >> 2) & 1);
          const uint32_t da = desc_lo(sb + st * G_ST + wg * 8192, 16), db = desc_lo(sb + st * G_ST + 16384, 8192);
          wgmma_fence();
#pragma unroll
          for (int k = 0; k < 4; k++) wgmma_m64n256k16_ss<1>(acc, da + k * 2, db + k * 128, (kb | k) != 0);
          wgmma_commit();
          if (kb > 0) { wgmma_wait<1>(); g_release((kb - 1) & 3); }
          if (kb == 0 && i > 0) put_tile(0);
          if (kb == 4 && i > 0) put_tile(1);
        }
        wgmma_wait<0>();
        g_release(3);
        fence_regs(acc);
#pragma unroll
        for (int k = 0; k < 64; k++) pk[k] = pack_bf16(acc[2 * k], acc[2 * k + 1]);
        if (threadIdx.x == 0) PROF_0(1 + i);
      }
      int prev = 0;
#pragma unroll
      for (int kb = 0; kb < 8; kb++) {
        mbar_wait<22>(sb + B_SF + 8 * sl, ph);
        wgmma_fence();
        issue128<0>(s, sb + sl * S_ST, wg, kb == 0);
        wgmma_commit();
        if (kb > 0) { wgmma_wait<1>(); s_release(prev); }
        prev = sl; s_nxt();
        if (kb == 0) put_tile(0);
        if (kb == 4) put_tile(1);
      }
      wgmma_wait<0>();
      fence_regs(s);
      s_release(prev);
#pragma unroll
      for (int k = 0; k < 32; k++) qf[k] = pack_bf16(s[2 * k], s[2 * k + 1]);
    }
    if (threadIdx.x == 0) PROF_0(5);
    {
      float o[64]; uint32_t p[32];
      Softmax st; float al0 = 1.f, al1 = 1.f;
#pragma unroll
      for (int i = 0; i < 64; i++) o[i] = 0.f;
      if (wg == 1) named_bar_arrive(1, 256);
      for (int t = 0; t < 4; t++) {
        const int qb = attn_qblock(h, r, t);
        if (threadIdx.x == 0) PROF_T(6, t);
        mbar_wait<23>(sb + B_SF + 8 * sl, ph);
        if (threadIdx.x == 0) PROF_T(6, 4 + t);
        named_bar_sync(1 + wg, 256);
        wgmma_fence();
        issue_qk(s, qf, sb + sl * S_ST);
        wgmma_commit();
        named_bar_arrive(2 - wg, 256);
        wgmma_wait<0>(); fence_regs(s);
        s_release(sl); s_nxt();
        sm_first(s, st, row_in_blk, q);
        sm_exp<0, 16>(s, st);
        sm_sum_cvt(s, p, st);
        mbar_wait<24>(sb + B_SF + 8 * sl, ph);
        if (threadIdx.x == 0) PROF_T(6, 8 + t);
        for (int j = qb; j > 0; j--) {
          const int ks = sl; s_nxt();
          const int vs = sl;
          named_bar_sync(1 + wg, 256);
          wgmma_fence();
          issue_qk(s, qf, sb + ks * S_ST);
          wgmma_commit();
          mbar_wait<25>(sb + B_SF + 8 * vs, ph);
          s_nxt();
          wgmma_fence();
          issue_pv(o, p, sb + vs * S_ST, j != qb);
          wgmma_commit();
          named_bar_arrive(2 - wg, 256);
          wgmma_wait<1>(); fence_regs(s);
          s_release(ks);
          const bool bad = sm_next(s, st, al0, al1);
          sm_exp<0, 4>(s, st);
          fence_regs(s);
          mbar_wait<26>(sb + B_SF + 8 * sl, ph);
          wgmma_wait<0>(); fence_regs(o); fence_regs(p);
          s_release(vs);
          if (bad) {
#pragma unroll
            for (int i = 0; i < 16; i++) { o[4 * i] *= al0; o[4 * i + 1] *= al0; o[4 * i + 2] *= al1; o[4 * i + 3] *= al1; }
          }
          sm_exp<4, 16>(s, st);
          sm_sum_cvt(s, p, st);
        }
        if (threadIdx.x == 0) PROF_0(6 + t);
        const int vs = sl; s_nxt();
        named_bar_sync(1 + wg, 256);
        wgmma_fence();
        issue_pv(o, p, sb + vs * S_ST, qb != 0);
        wgmma_commit();
        if (t < 3 || wg == 0) named_bar_arrive(2 - wg, 256);
        float l0 = st.l0, l1 = st.l1;
        const int nkb = t < 3 ? 8 : 32;
        mbar_wait<27>(sb + B_SF + 8 * sl, ph);
        wgmma_fence();
        issue128<0>(s, sb + sl * S_ST, wg, true);
        wgmma_commit();
        int prev = sl; s_nxt();
        l0 += __shfl_xor_sync(0xffffffffu, l0, 1); l1 += __shfl_xor_sync(0xffffffffu, l1, 1);
        l0 += __shfl_xor_sync(0xffffffffu, l0, 2); l1 += __shfl_xor_sync(0xffffffffu, l1, 2);
        const float i0 = 1.f / l0, i1 = 1.f / l1;
        wgmma_wait<1>(); fence_regs(o); fence_regs(p);
        s_release(vs);
        auto put_ctx = [&](int jp) {
          stg_put(jp >> 2, jp, pack_bf16(o[8 * jp] * i0, o[8 * jp + 1] * i0), pack_bf16(o[8 * jp + 2] * i1, o[8 * jp + 3] * i1),
                  pack_bf16(o[8 * jp + 4] * i0, o[8 * jp + 5] * i0), pack_bf16(o[8 * jp + 6] * i1, o[8 * jp + 7] * i1));
        };
        stg_acquire();
        put_ctx(0); put_ctx(1);
        mbar_wait<28>(sb + B_SF + 8 * sl, ph);
        wgmma_fence();
        issue128<0>(s, sb + sl * S_ST, wg, false);
        wgmma_commit();
        put_ctx(2); put_ctx(3); put_ctx(4);
        wgmma_wait<1>(); s_release(prev); prev = sl; s_nxt();
        mbar_wait<28>(sb + B_SF + 8 * sl, ph);
        wgmma_fence();
        issue128<0>(s, sb + sl * S_ST, wg, false);
        wgmma_commit();
        put_ctx(5); put_ctx(6); put_ctx(7);
        stg_publish();
        wgmma_wait<1>(); s_release(prev); prev = sl; s_nxt();
        for (int kb = 3; kb < nkb; kb++) {
          mbar_wait<29>(sb + B_SF + 8 * sl, ph);
          wgmma_fence();
          issue128<0>(s, sb + sl * S_ST, wg, false);
          wgmma_commit();
          wgmma_wait<1>(); s_release(prev); prev = sl; s_nxt();
        }
        wgmma_wait<0>();
        fence_regs(s);
        s_release(prev);
#pragma unroll
        for (int k = 0; k < 32; k++) qf[k] = pack_bf16(s[2 * k], s[2 * k + 1]);
      }
    }
    if (threadIdx.x == 0) PROF_0(10);
#pragma unroll
    for (int st = 0; st < 4; st++) g_release(st);
    uint32_t xr[16];
    {
      const uint32_t* xs = reinterpret_cast<const uint32_t*>(ptrs.x + (tm * 128 + row_in_blk) * DM + tn * 128 + rho * 64 + 2 * q);
#pragma unroll
      for (int j = 0; j < 8; j++) { xr[2 * j] = __ldg(xs + 4 * j); xr[2 * j + 1] = __ldg(xs + 8 * (DM / 2) + 4 * j); }
    }

    const uint32_t xbuf = stg + (threadIdx.x & 127) * 16;
    const uint32_t xbuf_peer = mapa(xbuf, rho ^ 1), xf_peer = mapa(sb + B_XF + 8 * wg, rho ^ 1);
    auto exchange = [&](float (&d)[64], float (&v)[32], uint32_t par) {
      if ((threadIdx.x & 127) == 0) mbar_expect_tx(sb + B_XF + 8 * wg, 16384);
      mbar_wait_cl<30>(sb + B_XR + 8 * wg, par);
      if (threadIdx.x == 0) PROF_T(7, 8 + par * 16);
#pragma unroll
      for (int i = 0; i < 8; i++)
        st_async_v4(xbuf_peer + i * 2048, rho ? d[4 * i] : d[32 + 4 * i], rho ? d[4 * i + 1] : d[33 + 4 * i],
                    rho ? d[4 * i + 2] : d[34 + 4 * i], rho ? d[4 * i + 3] : d[35 + 4 * i], xf_peer);
#pragma unroll
      for (int i = 0; i < 32; i++) v[i] = rho ? d[32 + i] : d[i];
    };
    auto exchange_finish = [&](float (&v)[32], uint32_t par) {
      if (threadIdx.x == 0) PROF_T(7, 9 + par * 16);
      mbar_wait_cl<31>(sb + B_XF + 8 * wg, par);
      if (threadIdx.x == 0) PROF_T(7, 10 + par * 16);
#pragma unroll
      for (int i = 0; i < 8; i++) {
        const float4 u = lds_v4(xbuf + i * 2048);
        v[4 * i] += u.x; v[4 * i + 1] += u.y; v[4 * i + 2] += u.z; v[4 * i + 3] += u.w;
      }
    };
    {
      float v[32];
      exchange(s, v, 0);
      stg_acquire();
      exchange_finish(v, 0);
      uint32_t hp[16];
      float s0 = 0.f, s1 = 0.f;
#pragma unroll
      for (int j = 0; j < 8; j++) {
        hp[2 * j] = pack_bf16(bf16lo(xr[2 * j]) + v[4 * j], bf16hi(xr[2 * j]) + v[4 * j + 1]);
        hp[2 * j + 1] = pack_bf16(bf16lo(xr[2 * j + 1]) + v[4 * j + 2], bf16hi(xr[2 * j + 1]) + v[4 * j + 3]);
        s0 += bf16lo(hp[2 * j]) + bf16hi(hp[2 * j]); s1 += bf16lo(hp[2 * j + 1]) + bf16hi(hp[2 * j + 1]);
      }
      if (threadIdx.x == 0) PROF_T(7, 11);
      named_bar_sync(3 + wg, 128);
      if (threadIdx.x == 0) PROF_T(7, 12);
#pragma unroll
      for (int jp = 0; jp < 4; jp++) stg_put(0, jp, hp[4 * jp], hp[4 * jp + 1], hp[4 * jp + 2], hp[4 * jp + 3]);
      s0 += __shfl_xor_sync(0xffffffffu, s0, 1); s1 += __shfl_xor_sync(0xffffffffu, s1, 1);
      s0 += __shfl_xor_sync(0xffffffffu, s0, 2); s1 += __shfl_xor_sync(0xffffffffu, s1, 2);
      s0 *= (1.f / 64.f); s1 *= (1.f / 64.f);
      float m0 = 0.f, m1 = 0.f;
#pragma unroll
      for (int j = 0; j < 8; j++) {
        const float a = bf16lo(hp[2 * j]) - s0, c = bf16hi(hp[2 * j]) - s0, d = bf16lo(hp[2 * j + 1]) - s1, e = bf16hi(hp[2 * j + 1]) - s1;
        m0 += a * a + c * c; m1 += d * d + e * e;
      }
      m0 += __shfl_xor_sync(0xffffffffu, m0, 1); m1 += __shfl_xor_sync(0xffffffffu, m1, 1);
      m0 += __shfl_xor_sync(0xffffffffu, m0, 2); m1 += __shfl_xor_sync(0xffffffffu, m1, 2);
      if (q == 0) {
        const uint32_t a = stg + 8192 + (warp * 16 + (lane >> 2)) * 8;
        sts_v2(a, s0, m0); sts_v2(a + 64, s1, m1);
      }
      if (threadIdx.x == 0) PROF_T(7, 13);
      stg_publish();
    }
    if (threadIdx.x == 0) PROF_0(11);
    {
      float mu0, mu1, rs0, rs1;
      const uint32_t csb = sb + O_CS + q * 8;
      auto glu2 = [&](float g0, float g1, float u0, float u1, float2 cg, float2 cu, float nmu, float hrs) -> uint32_t {
        const float t0 = tanh_approx(hrs * fmaf(nmu, cg.x, g0)), t1 = tanh_approx(hrs * fmaf(nmu, cg.y, g1));
        const float w0 = fmaf(nmu, cu.x, u0), w1 = fmaf(nmu, cu.y, u1);
        return pack_bf16(hrs * fmaf(t0, w0, w0), hrs * fmaf(t1, w1, w1));
      };
      {
        float acc[128];
#pragma unroll
        for (int kb = 0; kb < 8; kb++) {
          const int st = kb & 3;
          mbar_wait<32>(sb + B_GF + 8 * st, (kb >> 2) & 1);
          const uint32_t da = desc_lo(sb + st * G_ST + wg * 8192, 16), db = desc_lo(sb + st * G_ST + 16384, 8192);
          wgmma_fence();
#pragma unroll
          for (int k = 0; k < 4; k++) wgmma_m64n256k16_ss<1>(acc, da + k * 2, db + k * 128, (kb | k) != 0);
          wgmma_commit();
          if (kb > 0) { wgmma_wait<1>(); g_release((kb - 1) & 3); }
          if (kb == 0) {
            const float2* sp = g_stats + (tm * 8 + 2 * q) * 128 + row_in_blk;
            const float2 a0 = ld_cg_f2(sp), a1 = ld_cg_f2(sp + 128), c0 = ld_cg_f2(sp + 8), c1 = ld_cg_f2(sp + 136);
            float t0 = a0.x + a1.x, t1 = c0.x + c1.x;
            t0 += __shfl_xor_sync(0xffffffffu, t0, 1); t1 += __shfl_xor_sync(0xffffffffu, t1, 1);
            t0 += __shfl_xor_sync(0xffffffffu, t0, 2); t1 += __shfl_xor_sync(0xffffffffu, t1, 2);
            mu0 = t0 * 0.125f; mu1 = t1 * 0.125f;
            float v0 = a0.y + a1.y + 64.f * ((a0.x - mu0) * (a0.x - mu0) + (a1.x - mu0) * (a1.x - mu0));
            float v1 = c0.y + c1.y + 64.f * ((c0.x - mu1) * (c0.x - mu1) + (c1.x - mu1) * (c1.x - mu1));
            v0 += __shfl_xor_sync(0xffffffffu, v0, 1); v1 += __shfl_xor_sync(0xffffffffu, v1, 1);
            v0 += __shfl_xor_sync(0xffffffffu, v0, 2); v1 += __shfl_xor_sync(0xffffffffu, v1, 2);
            rs0 = 0.5f * rsqrtf(v0 * (1.f / 512.f) + 1e-5f); rs1 = 0.5f * rsqrtf(v1 * (1.f / 512.f) + 1e-5f);
            mu0 = -mu0; mu1 = -mu1;
          }
        }
        wgmma_wait<0>();
        g_release(3);
        fence_regs(acc);
        mbar_wait<33>(sb + B_CS, 0);
        stg_acquire();
#pragma unroll
        for (int jp = 0; jp < 8; jp++) {
          const int j = 2 * jp;
          const float2 cg = lds_v2(csb + j * 32), cu = lds_v2(csb + 896 + j * 32);
          const float2 dg = lds_v2(csb + j * 32 + 32), du = lds_v2(csb + 896 + j * 32 + 32);
          stg_put(jp >> 2, jp, glu2(acc[4 * j], acc[4 * j + 1], acc[64 + 4 * j], acc[64 + 4 * j + 1], cg, cu, mu0, rs0),
                  glu2(acc[4 * j + 2], acc[4 * j + 3], acc[64 + 4 * j + 2], acc[64 + 4 * j + 3], cg, cu, mu1, rs1),
                  glu2(acc[4 * j + 4], acc[4 * j + 5], acc[64 + 4 * j + 4], acc[64 + 4 * j + 5], dg, du, mu0, rs0),
                  glu2(acc[4 * j + 6], acc[4 * j + 7], acc[64 + 4 * j + 6], acc[64 + 4 * j + 7], dg, du, mu1, rs1));
        }
      }
      if (threadIdx.x == 0) PROF_0(12);
      {
        float agu[96];
        float* const ag = agu; float* const au = agu + 48;
#pragma unroll
        for (int kb = 0; kb < 8; kb++) {
          const int st = kb & 3;
          mbar_wait<34>(sb + B_GF + 8 * st, (kb >> 2) & 1);
          const uint32_t da = desc_lo(sb + st * G_ST + wg * 8192, 16), db = desc_lo(sb + st * G_ST + 16384, 4096);
          wgmma_fence();
#pragma unroll
          for (int k = 0; k < 4; k++) wgmma_m64n192k16_ss64<1>(agu, da + k * 2, db + k * 64, (kb | k) != 0);
          wgmma_commit();
          if (kb == 0) stg_publish();
          if (kb > 0) { wgmma_wait<1>(); g_release((kb - 1) & 3); }
        }
        wgmma_wait<0>();
        g_release(3);
        fence_regs(agu);
        if (lane == 0) PROF_T(7, wg * 4 + warp);
        stg_acquire();
#pragma unroll
        for (int jp = 0; jp < 6; jp++) {
          const int j = 2 * jp;
          const float2 cg = lds_v2(csb + 512 + j * 32), cu = lds_v2(csb + 896 + 512 + j * 32);
          const float2 dg = lds_v2(csb + 512 + j * 32 + 32), du = lds_v2(csb + 896 + 512 + j * 32 + 32);
          const uint32_t a = glu2(ag[4 * j], ag[4 * j + 1], au[4 * j], au[4 * j + 1], cg, cu, mu0, rs0);
          const uint32_t c = glu2(ag[4 * j + 2], ag[4 * j + 3], au[4 * j + 2], au[4 * j + 3], cg, cu, mu1, rs1);
          const uint32_t d = glu2(ag[4 * j + 4], ag[4 * j + 5], au[4 * j + 4], au[4 * j + 5], dg, du, mu0, rs0);
          const uint32_t e = glu2(ag[4 * j + 6], ag[4 * j + 7], au[4 * j + 6], au[4 * j + 7], dg, du, mu1, rs1);
          if (jp < 4) stg_put(0, jp, a, c, d, e);
          if (jp >= 2) stg_put(1, jp - 2, a, c, d, e);
        }
        stg_publish();
      }
      if (threadIdx.x == 0) PROF_0(13);
      if (lane == 0) PROF_T(7, 16 + wg * 4 + warp);
      uint32_t hr[16];
      mbar_wait<35>(sb + B_SF + 8 * sl, ph);
      wgmma_fence();
      issue128<0>(s, sb + sl * S_ST, wg, true);
      wgmma_commit();
      int prev = sl; s_nxt();
#pragma unroll 1
      for (int kb = 1; kb < 8; kb++) {
        mbar_wait<35>(sb + B_SF + 8 * sl, ph);
        wgmma_fence();
        issue128<0>(s, sb + sl * S_ST, wg, false);
        wgmma_commit();
        wgmma_wait<1>(); s_release(prev);
        prev = sl; s_nxt();
      }
      {
        const uint32_t* hs = reinterpret_cast<const uint32_t*>(((ALIAS & 2) ? g_xn : g_h) + (tm * 128 + row_in_blk) * DM + tn * 128 + rho * 64 + 2 * q);
#pragma unroll
        for (int j = 0; j < 8; j++) { hr[2 * j] = ld_cg_u32(hs + 4 * j); hr[2 * j + 1] = ld_cg_u32(hs + 8 * (DM / 2) + 4 * j); }
      }
#pragma unroll 1
      for (int j = 0; j < 6; j++) {
        mbar_wait<36>(sb + B_SF + 8 * sl, ph);
        wgmma_fence();
        issue128h(s, sb + sl * S_ST, wg);
        wgmma_commit();
        wgmma_wait<1>(); s_release(prev); prev = sl; s_nxt();
      }
      wgmma_wait<0>();
      fence_regs(s);
      s_release(prev);
      if (threadIdx.x == 0) PROF_0(14);
      float v[32];
      exchange(s, v, 1);
      exchange_finish(v, 1);
      asm volatile("barrier.cluster.arrive.relaxed.aligned;" ::: "memory");
      uint32_t op[16];
#pragma unroll
      for (int j = 0; j < 8; j++) {
        op[2 * j] = pack_bf16(bf16lo(hr[2 * j]) + v[4 * j], bf16hi(hr[2 * j]) + v[4 * j + 1]);
        op[2 * j + 1] = pack_bf16(bf16lo(hr[2 * j + 1]) + v[4 * j + 2], bf16hi(hr[2 * j + 1]) + v[4 * j + 3]);
      }
      named_bar_sync(3 + wg, 128);
#pragma unroll
      for (int jp = 0; jp < 4; jp++) stg_put(0, jp, op[4 * jp], op[4 * jp + 1], op[4 * jp + 2], op[4 * jp + 3]);
      __syncwarp();
#pragma unroll
      for (int i = 0; i < 4; i++) {
        const int rr = warp * 16 + i * 4 + (lane >> 3);
        uint4 u;
        asm volatile("ld.shared.v4.u32 {%0, %1, %2, %3}, [%4];" : "=r"(u.x), "=r"(u.y), "=r"(u.z), "=r"(u.w) : "r"(stg + rr * 128 + (((lane ^ rr) & 7) << 4)) : "memory");
        *reinterpret_cast<uint4*>(ptrs.out + (tm * 128 + wg * 64 + rr) * DM + tn * 128 + rho * 64 + (lane & 7) * 8) = u;
      }
    }
    if (threadIdx.x == 0) { PROF_0(15); PROF_G(0, 17); }
    PROF_DUMP();
    asm volatile("barrier.cluster.wait.aligned;" ::: "memory");
  }
}

typedef CUresult (*PFN_encodeTiled_t)(CUtensorMap*, CUtensorMapDataType, cuuint32_t, void*, const cuuint64_t*, const cuuint64_t*,
                                      const cuuint32_t*, const cuuint32_t*, CUtensorMapInterleave, CUtensorMapSwizzle,
                                      CUtensorMapL2promotion, CUtensorMapFloatOOBfill);
static PFN_encodeTiled_t g_encode = nullptr;
static void make_map(CUtensorMap* m, const void* base, int rank, const cuuint64_t* dims, const cuuint64_t* strides, const cuuint32_t* box) {
  cuuint32_t es[5] = {1, 1, 1, 1, 1};
  g_encode(m, CU_TENSOR_MAP_DATA_TYPE_BFLOAT16, rank, const_cast<void*>(base), dims, strides, box, es, CU_TENSOR_MAP_INTERLEAVE_NONE,
           CU_TENSOR_MAP_SWIZZLE_128B, CU_TENSOR_MAP_L2_PROMOTION_L2_256B, CU_TENSOR_MAP_FLOAT_OOB_FILL_NONE);
}
static void map_2d(CUtensorMap* m, const void* base, int rows, int cols, int brows) {
  cuuint64_t d[2] = {(cuuint64_t)cols, (cuuint64_t)rows}, s[1] = {(cuuint64_t)cols * 2}; cuuint32_t b[2] = {64, (cuuint32_t)brows};
  make_map(m, base, 2, d, s, b);
}
static void map_2dp(CUtensorMap* m, const void* base, int rows, int cols, int pitch, int brows) {
  cuuint64_t d[2] = {(cuuint64_t)cols, (cuuint64_t)rows}, s[1] = {(cuuint64_t)pitch * 2}; cuuint32_t b[2] = {64, (cuuint32_t)brows};
  make_map(m, base, 2, d, s, b);
}
static void map_3d(CUtensorMap* m, const void* base, int rows, int cols, int brows) {
  cuuint64_t d[3] = {64, (cuuint64_t)rows, (cuuint64_t)(cols / 64)}, s[2] = {(cuuint64_t)cols * 2, 128}; cuuint32_t b[3] = {64, (cuuint32_t)brows, 2};
  make_map(m, base, 3, d, s, b);
}

static void map_3d32(CUtensorMap* m, const void* base, int rows, int cols) {
  cuuint64_t d[3] = {32, (cuuint64_t)rows, (cuuint64_t)(cols / 32)}, s[2] = {(cuuint64_t)cols * 2, 64}; cuuint32_t b[3] = {32, 64, 3}, es[3] = {1, 1, 1};
  g_encode(m, CU_TENSOR_MAP_DATA_TYPE_BFLOAT16, 3, const_cast<void*>(base), d, s, b, es, CU_TENSOR_MAP_INTERLEAVE_NONE,
           CU_TENSOR_MAP_SWIZZLE_64B, CU_TENSOR_MAP_L2_PROMOTION_L2_256B, CU_TENSOR_MAP_FLOAT_OOB_FILL_NONE);
}
static Maps g_maps;
static Ptrs g_ptrs;
static bool g_init = false;
static void* g_last_in[10];

extern "C" void kernel_launch(void* const* d_in, const int* in_sizes, int n_in, void* d_out, int out_size) {
  bool same = g_init;
  for (int i = 0; i < 10; i++) same = same && g_last_in[i] == d_in[i];
  if (!same) {
    for (int i = 0; i < 10; i++) g_last_in[i] = d_in[i];
    void* p = nullptr; cudaDriverEntryPointQueryResult qr;
    cudaGetDriverEntryPoint("cuTensorMapEncodeTiled", &p, cudaEnableDefault, &qr);
    g_encode = (PFN_encodeTiled_t)p;
    void *xn, *kk, *vv, *ctx, *hh, *act, *act1;
    cudaGetSymbolAddress(&xn, g_xn); cudaGetSymbolAddress(&kk, g_k); cudaGetSymbolAddress(&vv, g_v);
    cudaGetSymbolAddress(&ctx, g_ctx); cudaGetSymbolAddress(&hh, g_h); cudaGetSymbolAddress(&act, g_act); cudaGetSymbolAddress(&act1, g_act1);
    map_2d(&g_maps.ckv, d_in[1], SEQ, DM, 128);
    map_3d(&g_maps.wq, d_in[2], DM, HDALL, 64); map_3d(&g_maps.wk, d_in[3], DM, HDALL, 64); map_3d(&g_maps.wv, d_in[4], DM, HDALL, 64);
    map_2d(&g_maps.xn, xn, SEQ, DM, 128); map_2d(&g_maps.wq2, d_in[2], DM, HDALL, 64);
    map_3d(&g_maps.kst, kk, NH * SEQ, HD, 64); map_3d(&g_maps.vst, vv, NH * SEQ, HD, 64);
    map_3d(&g_maps.kld, kk, NH * SEQ, HD, 128); map_3d(&g_maps.vld, vv, NH * SEQ, HD, 128);
    map_3d(&g_maps.ctxst, ctx, SEQ, HDALL, 64); map_2d(&g_maps.ctxld, ctx, SEQ, HDALL, 128);
    map_3d(&g_maps.wo, d_in[5], HDALL, DM, 64);
    map_2d(&g_maps.h, hh, SEQ, DM, 64);
    map_2d(&g_maps.wg, d_in[7], DM, FF, 64); map_2d(&g_maps.wu, d_in[8], DM, FF, 64);
    map_3d32(&g_maps.wg32, d_in[7], DM, FF); map_3d32(&g_maps.wu32, d_in[8], DM, FF);
    map_2d(&g_maps.actst, act, SEQ, FF, 64); map_2d(&g_maps.actld, act, SEQ, FF, 128);
    map_3d(&g_maps.wd, d_in[9], FF, DM, 64); map_3d(&g_maps.wd32, d_in[9], FF, DM, 32);
    map_2d(&g_maps.act1st, act1, SEQ, 768, 64); map_2d(&g_maps.act1ld, act1, SEQ, 768, 128);
    map_2dp(&g_maps.actst, ctx, SEQ, FF, HDALL, 64); map_2dp(&g_maps.actld, ctx, SEQ, FF, HDALL, 128);
    map_2dp(&g_maps.act1st, (__nv_bfloat16*)ctx + 2048, SEQ, 768, HDALL, 64); map_2dp(&g_maps.act1ld, (__nv_bfloat16*)ctx + 2048, SEQ, 768, HDALL, 128);
    cudaFuncSetAttribute(k_mega, cudaFuncAttributeMaxDynamicSharedMemorySize, MK_SMEM);
    g_init = true;
  }
  g_ptrs.x = (const __nv_bfloat16*)d_in[0]; g_ptrs.wg = (const __nv_bfloat16*)d_in[7]; g_ptrs.wu = (const __nv_bfloat16*)d_in[8];
  g_ptrs.wo = (const __nv_bfloat16*)d_in[5]; g_ptrs.wd = (const __nv_bfloat16*)d_in[9]; g_ptrs.out = (__nv_bfloat16*)d_out;
  g_ptrs.ckv = (const __nv_bfloat16*)d_in[1]; g_ptrs.wk = (const __nv_bfloat16*)d_in[3]; g_ptrs.wv = (const __nv_bfloat16*)d_in[4];
  k_mega<<<128, 384, MK_SMEM, cudaStreamPerThread>>>(g_maps, g_ptrs);
}
```

```cpp
#include <cuda_runtime.h>
#include <cuda_bf16.h>
#include <cuda.h>
#include <stdint.h>

constexpr int SEQ = 2048, DM = 512, NH = 32, HD = 128, HDALL = 4096, FF = 1792;

__device__ __forceinline__ uint32_t smem_u32(const void* p) { return (uint32_t)__cvta_generic_to_shared(p); }
__device__ __forceinline__ void mbar_init(uint32_t bar, uint32_t count) {
  asm volatile("mbarrier.init.shared::cta.b64 [%0], %1;" :: "r"(bar), "r"(count) : "memory");
}
__device__ __forceinline__ void mbar_expect_tx(uint32_t bar, uint32_t bytes) {
  asm volatile("mbarrier.arrive.expect_tx.shared::cta.b64 _, [%0], %1;" :: "r"(bar), "r"(bytes) : "memory");
}
__device__ __forceinline__ void mbar_arrive(uint32_t bar) {
  asm volatile("mbarrier.arrive.shared::cta.b64 _, [%0];" :: "r"(bar) : "memory");
}

#define SPIN_LIMIT "2000000"
#define SPIN_DBG(IDOP, VALOP)
template<int ID> __device__ __forceinline__ void mbar_wait(uint32_t bar, uint32_t parity) {
  asm volatile("{\n.reg .pred p;\n.reg .u32 c;\nmov.u32 c, 0;\n"
    "LAB_WAIT:\n"
    "mbarrier.try_wait.parity.shared::cta.b64 p, [%0], %1;\n"
    "@p bra LAB_DONE;\n"
    "add.u32 c, c, 1;\n"
    SPIN_DBG("%2", "%1")
    "setp.gt.u32 p, c, " SPIN_LIMIT ";\n"
    "@p trap;\n"
    "bra LAB_WAIT;\n"
    "LAB_DONE:\n}" :: "r"(bar), "r"(parity), "n"(ID) : "memory");
}
template<int ID> __device__ __forceinline__ void mbar_spin(uint32_t bar, uint32_t parity) {
  asm volatile("{\n.reg .pred p;\n.reg .u32 c;\nmov.u32 c, 0;\n"
    "LAB_WAIT:\n"
    "mbarrier.test_wait.parity.shared::cta.b64 p, [%0], %1;\n"
    "@p bra LAB_DONE;\n"
    "add.u32 c, c, 1;\n"
    "setp.gt.u32 p, c, 40000000;\n"
    "@p trap;\n"
    "bra LAB_WAIT;\n"
    "LAB_DONE:\n}" :: "r"(bar), "r"(parity), "n"(ID) : "memory");
}
__device__ __forceinline__ void tma_load_2d(uint32_t dst, const CUtensorMap* m, uint32_t bar, int c0, int c1) {
  asm volatile("cp.async.bulk.tensor.2d.shared::cluster.global.mbarrier::complete_tx::bytes [%0], [%1, {%3, %4}], [%2];"
    :: "r"(dst), "l"(m), "r"(bar), "r"(c0), "r"(c1) : "memory");
}
__device__ __forceinline__ void tma_load_3d(uint32_t dst, const CUtensorMap* m, uint32_t bar, int c0, int c1, int c2) {
  asm volatile("cp.async.bulk.tensor.3d.shared::cluster.global.mbarrier::complete_tx::bytes [%0], [%1, {%3, %4, %5}], [%2];"
    :: "r"(dst), "l"(m), "r"(bar), "r"(c0), "r"(c1), "r"(c2) : "memory");
}
__device__ __forceinline__ void tma_load_5d(uint32_t dst, const CUtensorMap* m, uint32_t bar, int c0, int c1, int c2, int c3, int c4) {
  asm volatile("cp.async.bulk.tensor.5d.shared::cluster.global.mbarrier::complete_tx::bytes [%0], [%1, {%3, %4, %5, %6, %7}], [%2];"
    :: "r"(dst), "l"(m), "r"(bar), "r"(c0), "r"(c1), "r"(c2), "r"(c3), "r"(c4) : "memory");
}
__device__ __forceinline__ void prefetch_tmap(const CUtensorMap* m) {
  asm volatile("prefetch.tensormap [%0];" :: "l"(m) : "memory");
}
__device__ __forceinline__ void wgmma_fence() { asm volatile("wgmma.fence.sync.aligned;" ::: "memory"); }
__device__ __forceinline__ void wgmma_commit() { asm volatile("wgmma.commit_group.sync.aligned;" ::: "memory"); }
template<int N> __device__ __forceinline__ void wgmma_wait() { asm volatile("wgmma.wait_group.sync.aligned %0;" :: "n"(N) : "memory"); }
template<int R> __device__ __forceinline__ void reg_alloc() { asm volatile("setmaxnreg.inc.sync.aligned.u32 %0;" :: "n"(R)); }
template<int R> __device__ __forceinline__ void reg_dealloc() { asm volatile("setmaxnreg.dec.sync.aligned.u32 %0;" :: "n"(R)); }
__device__ __forceinline__ void named_bar_sync(int id, int n) { asm volatile("bar.sync %0, %1;" :: "r"(id), "r"(n) : "memory"); }
__device__ __forceinline__ void named_bar_arrive(int id, int n) { asm volatile("bar.arrive %0, %1;" :: "r"(id), "r"(n) : "memory"); }
__device__ __forceinline__ uint64_t make_desc(uint32_t addr, uint32_t lbo_bytes, uint32_t sbo_bytes) {
  uint64_t d = 0;
  d |= (uint64_t)((addr & 0x3FFFF) >> 4);
  d |= (uint64_t)(lbo_bytes >> 4) << 16;
  d |= (uint64_t)(sbo_bytes >> 4) << 32;
  d |= (uint64_t)1 << 62;
  return d;
}
__device__ __forceinline__ uint32_t desc_lo(uint32_t addr, uint32_t lbo_bytes) { return ((addr & 0x3FFFF) >> 4) + ((lbo_bytes >> 4) << 16); }
template<int N> __device__ __forceinline__ void fence_regs(float (&d)[N]) {
#pragma unroll
  for (int i = 0; i < N; i++) asm volatile("" : "+f"(d[i]) :: "memory");
}
template<int N> __device__ __forceinline__ void fence_regs(uint32_t (&d)[N]) {
#pragma unroll
  for (int i = 0; i < N; i++) asm volatile("" : "+r"(d[i]) :: "memory");
}
__device__ __forceinline__ uint32_t pack_bf16(float lo, float hi) {
  uint32_t r; asm("cvt.rn.bf16x2.f32 %0, %1, %2;" : "=r"(r) : "f"(hi), "f"(lo)); return r;
}
__device__ __forceinline__ float ex2(float x) { float y; asm("ex2.approx.ftz.f32 %0, %1;" : "=f"(y) : "f"(x)); return y; }
__device__ __forceinline__ float tanh_approx(float x) { float y; asm("tanh.approx.f32 %0, %1;" : "=f"(y) : "f"(x)); return y; }
__device__ __forceinline__ float bf16lo(uint32_t v) { return __uint_as_float(v << 16); }
__device__ __forceinline__ float bf16hi(uint32_t v) { return __uint_as_float(v & 0xffff0000u); }

__device__ __forceinline__ uint32_t mapa(uint32_t addr, uint32_t cta) {
  uint32_t r; asm("mapa.shared::cluster.u32 %0, %1, %2;" : "=r"(r) : "r"(addr), "r"(cta)); return r;
}
__device__ __forceinline__ void mbar_arrive_cl(uint32_t cluster_addr) {
  asm volatile("mbarrier.arrive.shared::cluster.b64 _, [%0];" :: "r"(cluster_addr) : "memory");
}
template<int ID> __device__ __forceinline__ void mbar_wait_cl(uint32_t bar, uint32_t parity) {
  asm volatile("{\n.reg .pred p;\n.reg .u32 c;\nmov.u32 c, 0;\n"
    "LAB_WAIT:\n"
    "mbarrier.try_wait.parity.acquire.cluster.shared::cta.b64 p, [%0], %1;\n"
    "@p bra LAB_DONE;\n"
    "add.u32 c, c, 1;\n"
    SPIN_DBG("%2", "%1")
    "setp.gt.u32 p, c, " SPIN_LIMIT ";\n"
    "@p trap;\n"
    "bra LAB_WAIT;\n"
    "LAB_DONE:\n}" :: "r"(bar), "r"(parity), "n"(ID) : "memory");
}
__device__ __forceinline__ void tma_load_2d_mc(uint32_t dst, const CUtensorMap* m, uint32_t bar, int c0, int c1) {
  asm volatile("cp.async.bulk.tensor.2d.shared::cluster.global.mbarrier::complete_tx::bytes.multicast::cluster [%0], [%1, {%3, %4}], [%2], %5;"
    :: "r"(dst), "l"(m), "r"(bar), "r"(c0), "r"(c1), "h"((uint16_t)3) : "memory");
}
__device__ __forceinline__ void tma_load_3d_mc(uint32_t dst, const CUtensorMap* m, uint32_t bar, int c0, int c1, int c2) {
  asm volatile("cp.async.bulk.tensor.3d.shared::cluster.global.mbarrier::complete_tx::bytes.multicast::cluster [%0], [%1, {%3, %4, %5}], [%2], %6;"
    :: "r"(dst), "l"(m), "r"(bar), "r"(c0), "r"(c1), "r"(c2), "h"((uint16_t)3) : "memory");
}
__device__ __forceinline__ void tma_store_2d(const CUtensorMap* m, uint32_t src, int c0, int c1) {
  asm volatile("cp.async.bulk.tensor.2d.global.shared::cta.bulk_group [%0, {%2, %3}], [%1];" :: "l"(m), "r"(src), "r"(c0), "r"(c1) : "memory");
}
__device__ __forceinline__ void tma_store_3d(const CUtensorMap* m, uint32_t src, int c0, int c1, int c2) {
  asm volatile("cp.async.bulk.tensor.3d.global.shared::cta.bulk_group [%0, {%2, %3, %4}], [%1];" :: "l"(m), "r"(src), "r"(c0), "r"(c1), "r"(c2) : "memory");
}
__device__ __forceinline__ void bulk_store(void* gdst, uint32_t src, uint32_t bytes) {
  asm volatile("cp.async.bulk.global.shared::cta.bulk_group [%0], [%1], %2;" :: "l"(gdst), "r"(src), "r"(bytes) : "memory");
}
__device__ __forceinline__ void bulk_load(uint32_t dst, const void* gsrc, uint32_t bytes, uint32_t bar) {
  asm volatile("cp.async.bulk.shared::cluster.global.mbarrier::complete_tx::bytes [%0], [%1], %2, [%3];" :: "r"(dst), "l"(gsrc), "r"(bytes), "r"(bar) : "memory");
}
__device__ __forceinline__ void prefetch_3d(const CUtensorMap* m, int c0, int c1, int c2) {
  asm volatile("cp.async.bulk.prefetch.tensor.3d.L2.global [%0, {%1, %2, %3}];" :: "l"(m), "r"(c0), "r"(c1), "r"(c2) : "memory");
}
__device__ __forceinline__ void prefetch_2d(const CUtensorMap* m, int c0, int c1) {
  asm volatile("cp.async.bulk.prefetch.tensor.2d.L2.global [%0, {%1, %2}];" :: "l"(m), "r"(c0), "r"(c1) : "memory");
}
__device__ __forceinline__ void bulk_commit() { asm volatile("cp.async.bulk.commit_group;" ::: "memory"); }
__device__ __forceinline__ void bulk_wait_read() { asm volatile("cp.async.bulk.wait_group.read 0;" ::: "memory"); }
__device__ __forceinline__ void bulk_wait_all() { asm volatile("cp.async.bulk.wait_group 0;" ::: "memory"); }
__device__ __forceinline__ void fence_async_smem() { asm volatile("fence.proxy.async.shared::cta;" ::: "memory"); }
__device__ __forceinline__ void stmatrix_x4(uint32_t addr, uint32_t a, uint32_t b, uint32_t c, uint32_t d) {
  asm volatile("stmatrix.sync.aligned.m8n8.x4.shared.b16 [%0], {%1, %2, %3, %4};" :: "r"(addr), "r"(a), "r"(b), "r"(c), "r"(d) : "memory");
}
__device__ __forceinline__ void st_async_v4(uint32_t raddr, float a, float b, float c, float d, uint32_t rbar) {
  asm volatile("st.async.weak.shared::cluster.mbarrier::complete_tx::bytes.v4.f32 [%0], {%1, %2, %3, %4}, [%5];"
    :: "r"(raddr), "f"(a), "f"(b), "f"(c), "f"(d), "r"(rbar) : "memory");
}
__device__ __forceinline__ float4 lds_v4(uint32_t addr) {
  float4 v; asm volatile("ld.shared.v4.f32 {%0, %1, %2, %3}, [%4];" : "=f"(v.x), "=f"(v.y), "=f"(v.z), "=f"(v.w) : "r"(addr) : "memory"); return v;
}
__device__ __forceinline__ float2 lds_v2(uint32_t addr) {
  float2 v; asm volatile("ld.shared.v2.f32 {%0, %1}, [%2];" : "=f"(v.x), "=f"(v.y) : "r"(addr) : "memory"); return v;
}
__device__ __forceinline__ void sts_v2(uint32_t addr, float a, float b) {
  asm volatile("st.shared.v2.f32 [%0], {%1, %2};" :: "r"(addr), "f"(a), "f"(b) : "memory");
}
__device__ __forceinline__ void flag_arrive(uint32_t* p) {
  asm volatile("red.release.gpu.global.add.u32 [%0], 1;" :: "l"(p) : "memory");
}
__device__ __forceinline__ void flag_arrive_relaxed(uint32_t* p) {
  asm volatile("red.relaxed.gpu.global.add.u32 [%0], 1;" :: "l"(p) : "memory");
}
template<int ID> __device__ __forceinline__ void flag_wait_relaxed(const uint32_t* p, uint32_t target) {
  asm volatile("{\n.reg .pred p;\n.reg .u32 c, v;\nmov.u32 c, 0;\n"
    "LAB_WAIT:\n"
    "ld.relaxed.gpu.global.u32 v, [%0];\n"
    "sub.u32 v, v, %1;\n"
    "setp.ge.s32 p, v, 0;\n"
    "@p bra LAB_DONE;\n"
    "add.u32 c, c, 1;\n"
    SPIN_DBG("%2", "v")
    "setp.gt.u32 p, c, " SPIN_LIMIT ";\n"
    "@p trap;\n"
    "bra LAB_WAIT;\n"
    "LAB_DONE:\n}" :: "l"(p), "r"(target), "n"(ID) : "memory");
}
template<int ID> __device__ __forceinline__ void flag_wait(const uint32_t* p, uint32_t target) {
  asm volatile("{\n.reg .pred p;\n.reg .u32 c, v;\nmov.u32 c, 0;\n"
    "LAB_WAIT:\n"
    "ld.acquire.gpu.global.u32 v, [%0];\n"
    "sub.u32 v, v, %1;\n"
    "setp.ge.s32 p, v, 0;\n"
    "@p bra LAB_DONE;\n"
    "add.u32 c, c, 1;\n"
    SPIN_DBG("%2", "v")
    "setp.gt.u32 p, c, " SPIN_LIMIT ";\n"
    "@p trap;\n"
    "bra LAB_WAIT;\n"
    "LAB_DONE:\n"
    "fence.proxy.async.global;\n}"
    :: "l"(p), "r"(target), "n"(ID) : "memory");
}
__device__ __forceinline__ uint32_t ld_acquire_u32(const uint32_t* p) {
  uint32_t v; asm volatile("ld.acquire.gpu.global.u32 %0, [%1];" : "=r"(v) : "l"(p) : "memory");
  return v;
}
__device__ __forceinline__ bool flag_test(const uint32_t* p, uint32_t target) {
  uint32_t v; asm volatile("ld.acquire.gpu.global.u32 %0, [%1];" : "=r"(v) : "l"(p) : "memory");
  return (int32_t)(v - target) >= 0;
}
__device__ __forceinline__ bool mbar_test(uint32_t bar, uint32_t parity) {
  uint32_t r;
  asm volatile("{\n.reg .pred p;\nmbarrier.test_wait.parity.shared::cta.b64 p, [%1], %2;\nselp.u32 %0, 1, 0, p;\n}" : "=r"(r) : "r"(bar), "r"(parity) : "memory");
  return r != 0;
}
__device__ __forceinline__ void fence_async_global() { asm volatile("fence.proxy.async.global;" ::: "memory"); }
__device__ __forceinline__ void mbar_expect_only(uint32_t bar, uint32_t bytes) {
  asm volatile("mbarrier.expect_tx.relaxed.cta.shared::cta.b64 [%0], %1;" :: "r"(bar), "r"(bytes) : "memory");
}
__device__ __forceinline__ void prefetch_l2(const void* p, uint32_t bytes) {
  asm volatile("cp.async.bulk.prefetch.L2.global [%0], %1;" :: "l"(p), "r"(bytes) : "memory");
}
__device__ __forceinline__ void cluster_arrive() { asm volatile("barrier.cluster.arrive.release.aligned;" ::: "memory"); }
__device__ __forceinline__ void cluster_wait() { asm volatile("barrier.cluster.wait.acquire.aligned;" ::: "memory"); }

__device__ __forceinline__ void st_relaxed_v4(void* p, uint32_t a, uint32_t b, uint32_t c, uint32_t d) {
  asm volatile("st.relaxed.gpu.global.v4.u32 [%0], {%1, %2, %3, %4};" :: "l"(p), "r"(a), "r"(b), "r"(c), "r"(d) : "memory");
}
__device__ __forceinline__ void ld_nonzero_32(uint32_t (&u)[32], const void* p) {
  asm volatile("{\n.reg .pred p;\n.reg .u32 c, m;\nmov.u32 c, 0;\n"
    "LAB_WAIT:\n"
    "ld.relaxed.gpu.global.v4.u32 {%0, %1, %2, %3}, [%32+0];\n"
    "ld.relaxed.gpu.global.v4.u32 {%4, %5, %6, %7}, [%32+4096];\n"
    "ld.relaxed.gpu.global.v4.u32 {%8, %9, %10, %11}, [%32+8192];\n"
    "ld.relaxed.gpu.global.v4.u32 {%12, %13, %14, %15}, [%32+12288];\n"
    "ld.relaxed.gpu.global.v4.u32 {%16, %17, %18, %19}, [%32+16384];\n"
    "ld.relaxed.gpu.global.v4.u32 {%20, %21, %22, %23}, [%32+20480];\n"
    "ld.relaxed.gpu.global.v4.u32 {%24, %25, %26, %27}, [%32+24576];\n"
    "ld.relaxed.gpu.global.v4.u32 {%28, %29, %30, %31}, [%32+28672];\n"
    "min.u32 m, %0, %1;\n" "min.u32 m, m, %2;\n" "min.u32 m, m, %3;\n" "min.u32 m, m, %4;\n" "min.u32 m, m, %5;\n" "min.u32 m, m, %6;\n" "min.u32 m, m, %7;\n" "min.u32 m, m, %8;\n" "min.u32 m, m, %9;\n" "min.u32 m, m, %10;\n" "min.u32 m, m, %11;\n" "min.u32 m, m, %12;\n" "min.u32 m, m, %13;\n" "min.u32 m, m, %14;\n" "min.u32 m, m, %15;\n" "min.u32 m, m, %16;\n" "min.u32 m, m, %17;\n" "min.u32 m, m, %18;\n" "min.u32 m, m, %19;\n" "min.u32 m, m, %20;\n" "min.u32 m, m, %21;\n" "min.u32 m, m, %22;\n" "min.u32 m, m, %23;\n" "min.u32 m, m, %24;\n" "min.u32 m, m, %25;\n" "min.u32 m, m, %26;\n" "min.u32 m, m, %27;\n" "min.u32 m, m, %28;\n" "min.u32 m, m, %29;\n" "min.u32 m, m, %30;\n" "min.u32 m, m, %31;\n"
    "setp.ne.u32 p, m, 0;\n"
    "@p bra LAB_DONE;\n"
    "add.u32 c, c, 1;\n"
    "setp.gt.u32 p, c, " SPIN_LIMIT ";\n"
    "@p trap;\n"
    "bra LAB_WAIT;\n"
    "LAB_DONE:\n}" : "=&r"(u[0]), "=&r"(u[1]), "=&r"(u[2]), "=&r"(u[3]), "=&r"(u[4]), "=&r"(u[5]), "=&r"(u[6]), "=&r"(u[7]), "=&r"(u[8]), "=&r"(u[9]), "=&r"(u[10]), "=&r"(u[11]), "=&r"(u[12]), "=&r"(u[13]), "=&r"(u[14]), "=&r"(u[15]), "=&r"(u[16]), "=&r"(u[17]), "=&r"(u[18]), "=&r"(u[19]), "=&r"(u[20]), "=&r"(u[21]), "=&r"(u[22]), "=&r"(u[23]), "=&r"(u[24]), "=&r"(u[25]), "=&r"(u[26]), "=&r"(u[27]), "=&r"(u[28]), "=&r"(u[29]), "=&r"(u[30]), "=&r"(u[31]) : "l"(p) : "memory");
}
__device__ __forceinline__ void poll_v4(const void* p) {
  asm volatile("{\n.reg .pred p;\n.reg .u32 c, v;\nmov.u32 c, 0;\n"
    "LAB_WAIT:\n"
    "ld.relaxed.gpu.global.u32 v, [%0+12];\n"
    "setp.ne.u32 p, v, 0;\n"
    "@p bra LAB_DONE;\n"
    "add.u32 c, c, 1;\n"
    "setp.gt.u32 p, c, " SPIN_LIMIT ";\n"
    "@p trap;\n"
    "bra LAB_WAIT;\n"
    "LAB_DONE:\n}" :: "l"(p) : "memory");
}
__device__ __forceinline__ float2 ld_cg_f2(const void* p) {
  float2 v; asm volatile("ld.global.cg.v2.f32 {%0, %1}, [%2];" : "=f"(v.x), "=f"(v.y) : "l"(p) : "memory"); return v;
}
__device__ __forceinline__ uint32_t ld_cg_u32(const void* p) {
  uint32_t v; asm volatile("ld.global.cg.u32 %0, [%1];" : "=r"(v) : "l"(p) : "memory"); return v;
}
__device__ __forceinline__ uint64_t pol_first() { uint64_t p; asm("createpolicy.fractional.L2::evict_first.b64 %0, 1.0;" : "=l"(p)); return p; }
__device__ __forceinline__ uint64_t pol_normal() { uint64_t p; asm("createpolicy.fractional.L2::evict_normal.b64 %0, 1.0;" : "=l"(p)); return p; }
__device__ __forceinline__ void tma_load_2d_h(uint32_t dst, const CUtensorMap* m, uint32_t bar, int c0, int c1, uint64_t pol) {
  asm volatile("cp.async.bulk.tensor.2d.shared::cluster.global.mbarrier::complete_tx::bytes.L2::cache_hint [%0], [%1, {%3, %4}], [%2], %5;"
    :: "r"(dst), "l"(m), "r"(bar), "r"(c0), "r"(c1), "l"(pol) : "memory");
}
__device__ __forceinline__ void tma_load_3d_h(uint32_t dst, const CUtensorMap* m, uint32_t bar, int c0, int c1, int c2, uint64_t pol) {
  asm volatile("cp.async.bulk.tensor.3d.shared::cluster.global.mbarrier::complete_tx::bytes.L2::cache_hint [%0], [%1, {%3, %4, %5}], [%2], %6;"
    :: "r"(dst), "l"(m), "r"(bar), "r"(c0), "r"(c1), "r"(c2), "l"(pol) : "memory");
}
__device__ __forceinline__ void tma_load_3d_mc_h(uint32_t dst, const CUtensorMap* m, uint32_t bar, int c0, int c1, int c2, uint64_t pol) {
  asm volatile("cp.async.bulk.tensor.3d.shared::cluster.global.mbarrier::complete_tx::bytes.multicast::cluster.L2::cache_hint [%0], [%1, {%3, %4, %5}], [%2], %6, %7;"
    :: "r"(dst), "l"(m), "r"(bar), "r"(c0), "r"(c1), "r"(c2), "h"((uint16_t)3), "l"(pol) : "memory");
}
__device__ __forceinline__ void tma_store_3d_h(const CUtensorMap* m, uint32_t src, int c0, int c1, int c2, uint64_t pol) {
  asm volatile("cp.async.bulk.tensor.3d.global.shared::cta.bulk_group.L2::cache_hint [%0, {%2, %3, %4}], [%1], %5;" :: "l"(m), "r"(src), "r"(c0), "r"(c1), "r"(c2), "l"(pol) : "memory");
}
__device__ __forceinline__ uint4 ldg_v4_h(const void* p, uint64_t pol) {
  uint4 v; asm volatile("ld.global.nc.L2::cache_hint.v4.u32 {%0, %1, %2, %3}, [%4], %5;" : "=r"(v.x), "=r"(v.y), "=r"(v.z), "=r"(v.w) : "l"(p), "l"(pol)); return v;
}
__device__ __forceinline__ uint32_t ldg_h(const void* p, uint64_t pol) {
  uint32_t v; asm("ld.global.nc.L2::cache_hint.u32 %0, [%1], %2;" : "=r"(v) : "l"(p), "l"(pol)); return v;
}
__device__ __forceinline__ void ld2(bool ef, uint64_t pol, uint32_t dst, const CUtensorMap* m, uint32_t bar, int c0, int c1) {
  if (ef) tma_load_2d_h(dst, m, bar, c0, c1, pol); else tma_load_2d(dst, m, bar, c0, c1);
}
__device__ __forceinline__ void ld3(bool ef, uint64_t pol, uint32_t dst, const CUtensorMap* m, uint32_t bar, int c0, int c1, int c2) {
  if (ef) tma_load_3d_h(dst, m, bar, c0, c1, c2, pol); else tma_load_3d(dst, m, bar, c0, c1, c2);
}
__device__ __forceinline__ void ld3mc(bool ef, uint64_t pol, uint32_t dst, const CUtensorMap* m, uint32_t bar, int c0, int c1, int c2) {
  if (ef) tma_load_3d_mc_h(dst, m, bar, c0, c1, c2, pol); else tma_load_3d_mc(dst, m, bar, c0, c1, c2);
}
__device__ __forceinline__ uint64_t pol_unch() { uint64_t p; asm("createpolicy.fractional.L2::evict_normal.b64 %0, 1.0;" : "=l"(p)); return p; }
#define EVN 0
#define EVU 0
#define ALIAS 1
#define PUB 1
#define PUBM 31
#define EVF 91

#define PROF_T(k, i)
#define PROF_G(k, i)
#define PROF_0(i)
#define PROF_INIT()
#define PROF_DUMP()
template<int TB> __device__ __forceinline__ void wgmma_m64n128k16_ss(float (&d)[64], uint32_t da, uint32_t db, int scale_d) {
  asm volatile("{\n.reg .pred p;\n.reg .b64 da, db;\nsetp.ne.b32 p, %66, 0;\nmov.b64 da, {%64, 0x40000040};\nmov.b64 db, {%65, 0x40000040};\n"
    "wgmma.mma_async.sync.aligned.m64n128k16.f32.bf16.bf16 "
    "{%0, %1, %2, %3, %4, %5, %6, %7, %8, %9, %10, %11, %12, %13, %14, %15, "
    "%16, %17, %18, %19, %20, %21, %22, %23, %24, %25, %26, %27, %28, %29, %30, %31, "
    "%32, %33, %34, %35, %36, %37, %38, %39, %40, %41, %42, %43, %44, %45, %46, %47, "
    "%48, %49, %50, %51, %52, %53, %54, %55, %56, %57, %58, %59, %60, %61, %62, %63}, "
    "da, db, p, 1, 1, 0, %67;\n}\n"
    : "+f"(d[0]), "+f"(d[1]), "+f"(d[2]), "+f"(d[3]), "+f"(d[4]), "+f"(d[5]), "+f"(d[6]), "+f"(d[7]), "+f"(d[8]), "+f"(d[9]), "+f"(d[10]), "+f"(d[11]), "+f"(d[12]), "+f"(d[13]), "+f"(d[14]), "+f"(d[15]), "+f"(d[16]), "+f"(d[17]), "+f"(d[18]), "+f"(d[19]), "+f"(d[20]), "+f"(d[21]), "+f"(d[22]), "+f"(d[23]), "+f"(d[24]), "+f"(d[25]), "+f"(d[26]), "+f"(d[27]), "+f"(d[28]), "+f"(d[29]), "+f"(d[30]), "+f"(d[31]), "+f"(d[32]), "+f"(d[33]), "+f"(d[34]), "+f"(d[35]), "+f"(d[36]), "+f"(d[37]), "+f"(d[38]), "+f"(d[39]), "+f"(d[40]), "+f"(d[41]), "+f"(d[42]), "+f"(d[43]), "+f"(d[44]), "+f"(d[45]), "+f"(d[46]), "+f"(d[47]), "+f"(d[48]), "+f"(d[49]), "+f"(d[50]), "+f"(d[51]), "+f"(d[52]), "+f"(d[53]), "+f"(d[54]), "+f"(d[55]), "+f"(d[56]), "+f"(d[57]), "+f"(d[58]), "+f"(d[59]), "+f"(d[60]), "+f"(d[61]), "+f"(d[62]), "+f"(d[63])
    : "r"(da), "r"(db), "r"(scale_d), "n"(TB));
}
template<int TB> __device__ __forceinline__ void wgmma_m64n128k16_rs(float (&d)[64], uint32_t a0, uint32_t a1, uint32_t a2, uint32_t a3, uint32_t db, int scale_d) {
  asm volatile("{\n.reg .pred p;\n.reg .b64 db;\nsetp.ne.b32 p, %69, 0;\nmov.b64 db, {%68, 0x40000040};\n"
    "wgmma.mma_async.sync.aligned.m64n128k16.f32.bf16.bf16 "
    "{%0, %1, %2, %3, %4, %5, %6, %7, %8, %9, %10, %11, %12, %13, %14, %15, "
    "%16, %17, %18, %19, %20, %21, %22, %23, %24, %25, %26, %27, %28, %29, %30, %31, "
    "%32, %33, %34, %35, %36, %37, %38, %39, %40, %41, %42, %43, %44, %45, %46, %47, "
    "%48, %49, %50, %51, %52, %53, %54, %55, %56, %57, %58, %59, %60, %61, %62, %63}, "
    "{%64, %65, %66, %67}, db, p, 1, 1, %70;\n}\n"
    : "+f"(d[0]), "+f"(d[1]), "+f"(d[2]), "+f"(d[3]), "+f"(d[4]), "+f"(d[5]), "+f"(d[6]), "+f"(d[7]), "+f"(d[8]), "+f"(d[9]), "+f"(d[10]), "+f"(d[11]), "+f"(d[12]), "+f"(d[13]), "+f"(d[14]), "+f"(d[15]), "+f"(d[16]), "+f"(d[17]), "+f"(d[18]), "+f"(d[19]), "+f"(d[20]), "+f"(d[21]), "+f"(d[22]), "+f"(d[23]), "+f"(d[24]), "+f"(d[25]), "+f"(d[26]), "+f"(d[27]), "+f"(d[28]), "+f"(d[29]), "+f"(d[30]), "+f"(d[31]), "+f"(d[32]), "+f"(d[33]), "+f"(d[34]), "+f"(d[35]), "+f"(d[36]), "+f"(d[37]), "+f"(d[38]), "+f"(d[39]), "+f"(d[40]), "+f"(d[41]), "+f"(d[42]), "+f"(d[43]), "+f"(d[44]), "+f"(d[45]), "+f"(d[46]), "+f"(d[47]), "+f"(d[48]), "+f"(d[49]), "+f"(d[50]), "+f"(d[51]), "+f"(d[52]), "+f"(d[53]), "+f"(d[54]), "+f"(d[55]), "+f"(d[56]), "+f"(d[57]), "+f"(d[58]), "+f"(d[59]), "+f"(d[60]), "+f"(d[61]), "+f"(d[62]), "+f"(d[63])
    : "r"(a0), "r"(a1), "r"(a2), "r"(a3), "r"(db), "r"(scale_d), "n"(TB));
}
template<int TB> __device__ __forceinline__ void wgmma_m64n256k16_ss(float (&d)[128], uint32_t da, uint32_t db, int scale_d) {
  asm volatile("{\n.reg .pred p;\n.reg .b64 da, db;\nsetp.ne.b32 p, %130, 0;\nmov.b64 da, {%128, 0x40000040};\nmov.b64 db, {%129, 0x40000040};\n"
    "wgmma.mma_async.sync.aligned.m64n256k16.f32.bf16.bf16 "
    "{%0, %1, %2, %3, %4, %5, %6, %7, %8, %9, %10, %11, %12, %13, %14, %15, "
    "%16, %17, %18, %19, %20, %21, %22, %23, %24, %25, %26, %27, %28, %29, %30, %31, "
    "%32, %33, %34, %35, %36, %37, %38, %39, %40, %41, %42, %43, %44, %45, %46, %47, "
    "%48, %49, %50, %51, %52, %53, %54, %55, %56, %57, %58, %59, %60, %61, %62, %63, "
    "%64, %65, %66, %67, %68, %69, %70, %71, %72, %73, %74, %75, %76, %77, %78, %79, "
    "%80, %81, %82, %83, %84, %85, %86, %87, %88, %89, %90, %91, %92, %93, %94, %95, "
    "%96, %97, %98, %99, %100, %101, %102, %103, %104, %105, %106, %107, %108, %109, %110, %111, "
    "%112, %113, %114, %115, %116, %117, %118, %119, %120, %121, %122, %123, %124, %125, %126, %127}, "
    "da, db, p, 1, 1, 0, %131;\n}\n"
    : "+f"(d[0]), "+f"(d[1]), "+f"(d[2]), "+f"(d[3]), "+f"(d[4]), "+f"(d[5]), "+f"(d[6]), "+f"(d[7]), "+f"(d[8]), "+f"(d[9]), "+f"(d[10]), "+f"(d[11]), "+f"(d[12]), "+f"(d[13]), "+f"(d[14]), "+f"(d[15]), "+f"(d[16]), "+f"(d[17]), "+f"(d[18]), "+f"(d[19]), "+f"(d[20]), "+f"(d[21]), "+f"(d[22]), "+f"(d[23]), "+f"(d[24]), "+f"(d[25]), "+f"(d[26]), "+f"(d[27]), "+f"(d[28]), "+f"(d[29]), "+f"(d[30]), "+f"(d[31]), "+f"(d[32]), "+f"(d[33]), "+f"(d[34]), "+f"(d[35]), "+f"(d[36]), "+f"(d[37]), "+f"(d[38]), "+f"(d[39]), "+f"(d[40]), "+f"(d[41]), "+f"(d[42]), "+f"(d[43]), "+f"(d[44]), "+f"(d[45]), "+f"(d[46]), "+f"(d[47]), "+f"(d[48]), "+f"(d[49]), "+f"(d[50]), "+f"(d[51]), "+f"(d[52]), "+f"(d[53]), "+f"(d[54]), "+f"(d[55]), "+f"(d[56]), "+f"(d[57]), "+f"(d[58]), "+f"(d[59]), "+f"(d[60]), "+f"(d[61]), "+f"(d[62]), "+f"(d[63]), "+f"(d[64]), "+f"(d[65]), "+f"(d[66]), "+f"(d[67]), "+f"(d[68]), "+f"(d[69]), "+f"(d[70]), "+f"(d[71]), "+f"(d[72]), "+f"(d[73]), "+f"(d[74]), "+f"(d[75]), "+f"(d[76]), "+f"(d[77]), "+f"(d[78]), "+f"(d[79]), "+f"(d[80]), "+f"(d[81]), "+f"(d[82]), "+f"(d[83]), "+f"(d[84]), "+f"(d[85]), "+f"(d[86]), "+f"(d[87]), "+f"(d[88]), "+f"(d[89]), "+f"(d[90]), "+f"(d[91]), "+f"(d[92]), "+f"(d[93]), "+f"(d[94]), "+f"(d[95]), "+f"(d[96]), "+f"(d[97]), "+f"(d[98]), "+f"(d[99]), "+f"(d[100]), "+f"(d[101]), "+f"(d[102]), "+f"(d[103]), "+f"(d[104]), "+f"(d[105]), "+f"(d[106]), "+f"(d[107]), "+f"(d[108]), "+f"(d[109]), "+f"(d[110]), "+f"(d[111]), "+f"(d[112]), "+f"(d[113]), "+f"(d[114]), "+f"(d[115]), "+f"(d[116]), "+f"(d[117]), "+f"(d[118]), "+f"(d[119]), "+f"(d[120]), "+f"(d[121]), "+f"(d[122]), "+f"(d[123]), "+f"(d[124]), "+f"(d[125]), "+f"(d[126]), "+f"(d[127])
    : "r"(da), "r"(db), "r"(scale_d), "n"(TB));
}
template<int TB> __device__ __forceinline__ void wgmma_m64n96k16_ss(float (&d)[48], uint32_t da, uint32_t db, int scale_d) {
  asm volatile("{\n.reg .pred p;\n.reg .b64 da, db;\nsetp.ne.b32 p, %50, 0;\nmov.b64 da, {%48, 0x40000040};\nmov.b64 db, {%49, 0x40000040};\n"
    "wgmma.mma_async.sync.aligned.m64n96k16.f32.bf16.bf16 "
    "{%0, %1, %2, %3, %4, %5, %6, %7, %8, %9, %10, %11, %12, %13, %14, %15, "
    "%16, %17, %18, %19, %20, %21, %22, %23, %24, %25, %26, %27, %28, %29, %30, %31, "
    "%32, %33, %34, %35, %36, %37, %38, %39, %40, %41, %42, %43, %44, %45, %46, %47}, "
    "da, db, p, 1, 1, 0, %51;\n}\n"
    : "+f"(d[0]), "+f"(d[1]), "+f"(d[2]), "+f"(d[3]), "+f"(d[4]), "+f"(d[5]), "+f"(d[6]), "+f"(d[7]), "+f"(d[8]), "+f"(d[9]), "+f"(d[10]), "+f"(d[11]), "+f"(d[12]), "+f"(d[13]), "+f"(d[14]), "+f"(d[15]), "+f"(d[16]), "+f"(d[17]), "+f"(d[18]), "+f"(d[19]), "+f"(d[20]), "+f"(d[21]), "+f"(d[22]), "+f"(d[23]), "+f"(d[24]), "+f"(d[25]), "+f"(d[26]), "+f"(d[27]), "+f"(d[28]), "+f"(d[29]), "+f"(d[30]), "+f"(d[31]), "+f"(d[32]), "+f"(d[33]), "+f"(d[34]), "+f"(d[35]), "+f"(d[36]), "+f"(d[37]), "+f"(d[38]), "+f"(d[39]), "+f"(d[40]), "+f"(d[41]), "+f"(d[42]), "+f"(d[43]), "+f"(d[44]), "+f"(d[45]), "+f"(d[46]), "+f"(d[47])
    : "r"(da), "r"(db), "r"(scale_d), "n"(TB));
}
template<int TB> __device__ __forceinline__ void wgmma_m64n192k16_ss64(float (&d)[96], uint32_t da, uint32_t db, int scale_d) {
  asm volatile("{\n.reg .pred p;\n.reg .b64 da, db;\nsetp.ne.b32 p, %98, 0;\nmov.b64 da, {%96, 0x40000040};\nmov.b64 db, {%97, 0x80000020};\n"
    "wgmma.mma_async.sync.aligned.m64n192k16.f32.bf16.bf16 "
    "{%0, %1, %2, %3, %4, %5, %6, %7, %8, %9, %10, %11, %12, %13, %14, %15, %16, %17, %18, %19, %20, %21, %22, %23, %24, %25, %26, %27, %28, %29, %30, %31, %32, %33, %34, %35, %36, %37, %38, %39, %40, %41, %42, %43, %44, %45, %46, %47, %48, %49, %50, %51, %52, %53, %54, %55, %56, %57, %58, %59, %60, %61, %62, %63, %64, %65, %66, %67, %68, %69, %70, %71, %72, %73, %74, %75, %76, %77, %78, %79, %80, %81, %82, %83, %84, %85, %86, %87, %88, %89, %90, %91, %92, %93, %94, %95}, "
    "da, db, p, 1, 1, 0, %99;\n}"
    : "+f"(d[0]), "+f"(d[1]), "+f"(d[2]), "+f"(d[3]), "+f"(d[4]), "+f"(d[5]), "+f"(d[6]), "+f"(d[7]), "+f"(d[8]), "+f"(d[9]), "+f"(d[10]), "+f"(d[11]), "+f"(d[12]), "+f"(d[13]), "+f"(d[14]), "+f"(d[15]), "+f"(d[16]), "+f"(d[17]), "+f"(d[18]), "+f"(d[19]), "+f"(d[20]), "+f"(d[21]), "+f"(d[22]), "+f"(d[23]), "+f"(d[24]), "+f"(d[25]), "+f"(d[26]), "+f"(d[27]), "+f"(d[28]), "+f"(d[29]), "+f"(d[30]), "+f"(d[31]), "+f"(d[32]), "+f"(d[33]), "+f"(d[34]), "+f"(d[35]), "+f"(d[36]), "+f"(d[37]), "+f"(d[38]), "+f"(d[39]), "+f"(d[40]), "+f"(d[41]), "+f"(d[42]), "+f"(d[43]), "+f"(d[44]), "+f"(d[45]), "+f"(d[46]), "+f"(d[47]), "+f"(d[48]), "+f"(d[49]), "+f"(d[50]), "+f"(d[51]), "+f"(d[52]), "+f"(d[53]), "+f"(d[54]), "+f"(d[55]), "+f"(d[56]), "+f"(d[57]), "+f"(d[58]), "+f"(d[59]), "+f"(d[60]), "+f"(d[61]), "+f"(d[62]), "+f"(d[63]), "+f"(d[64]), "+f"(d[65]), "+f"(d[66]), "+f"(d[67]), "+f"(d[68]), "+f"(d[69]), "+f"(d[70]), "+f"(d[71]), "+f"(d[72]), "+f"(d[73]), "+f"(d[74]), "+f"(d[75]), "+f"(d[76]), "+f"(d[77]), "+f"(d[78]), "+f"(d[79]), "+f"(d[80]), "+f"(d[81]), "+f"(d[82]), "+f"(d[83]), "+f"(d[84]), "+f"(d[85]), "+f"(d[86]), "+f"(d[87]), "+f"(d[88]), "+f"(d[89]), "+f"(d[90]), "+f"(d[91]), "+f"(d[92]), "+f"(d[93]), "+f"(d[94]), "+f"(d[95])
    : "r"(da), "r"(db), "r"(scale_d), "n"(TB));
}
template<int TB> __device__ __forceinline__ void wgmma_m64n64k16_rs(float (&d)[64], uint32_t a0, uint32_t a1, uint32_t a2, uint32_t a3, uint32_t db, int scale_d) {
  asm volatile("{\n.reg .pred p;\n.reg .b64 db;\nsetp.ne.b32 p, %37, 0;\nmov.b64 db, {%36, 0x40000040};\n"
    "wgmma.mma_async.sync.aligned.m64n64k16.f32.bf16.bf16 "
    "{%0, %1, %2, %3, %4, %5, %6, %7, %8, %9, %10, %11, %12, %13, %14, %15, %16, %17, %18, %19, %20, %21, %22, %23, %24, %25, %26, %27, %28, %29, %30, %31}, "
    "{%32, %33, %34, %35}, db, p, 1, 1, %38;\n}\n"
    : "+f"(d[0]), "+f"(d[1]), "+f"(d[2]), "+f"(d[3]), "+f"(d[4]), "+f"(d[5]), "+f"(d[6]), "+f"(d[7]), "+f"(d[8]), "+f"(d[9]), "+f"(d[10]), "+f"(d[11]), "+f"(d[12]), "+f"(d[13]), "+f"(d[14]), "+f"(d[15]), "+f"(d[16]), "+f"(d[17]), "+f"(d[18]), "+f"(d[19]), "+f"(d[20]), "+f"(d[21]), "+f"(d[22]), "+f"(d[23]), "+f"(d[24]), "+f"(d[25]), "+f"(d[26]), "+f"(d[27]), "+f"(d[28]), "+f"(d[29]), "+f"(d[30]), "+f"(d[31])
    : "r"(a0), "r"(a1), "r"(a2), "r"(a3), "r"(db), "r"(scale_d), "n"(TB));
}
#define PFG 3
#define FLAG_WAIT flag_wait
__device__ __align__(1024) __nv_bfloat16 g_xn[SEQ * DM];
__device__ __align__(1024) __nv_bfloat16 g_k[NH * SEQ * HD];
__device__ __align__(1024) __nv_bfloat16 g_v[NH * SEQ * HD];
__device__ __align__(1024) __nv_bfloat16 g_ctx[SEQ * HDALL];
__device__ __align__(1024) __nv_bfloat16 g_h[SEQ * DM];
__device__ __align__(1024) __nv_bfloat16 g_act[SEQ * FF];
__device__ __align__(1024) __nv_bfloat16 g_act1[SEQ * 768];
__device__ __align__(1024) float g_cs[2 * FF];
__device__ __align__(1024) float2 g_stats[16 * 8 * 128];
__device__ __align__(1024) uint32_t g_sync[320 * 8];
__device__ unsigned long long g_ticket;
#define KVPERM 0x0321
#define PFQ 8
#define T0ORD 0x210
#define T0_GRP(v) ((T0ORD >> (4 * (v))) & 3)
#define KV_GRP(i) ((KVPERM >> (4 * (i))) & 3)
constexpr int C_XN = 0, C_CS = 16, C_KV = 32, C_CTX = 160, C_H = 224, C_ACT = 240;

struct Softmax { float m0, m1, mc0, mc1, l0, l1; int th0, th1; };
constexpr float SM_C = 0.08838834764831845f * 1.4426950408889634f;
constexpr float SM_TAU = 16.f;

__device__ __forceinline__ void row_max(const float (&s)[64], float& mx0, float& mx1) {
  float a0[4], a1[4];
#pragma unroll
  for (int i = 0; i < 4; i++) { a0[i] = fmaxf(s[4 * i], s[4 * i + 1]); a1[i] = fmaxf(s[4 * i + 2], s[4 * i + 3]); }
#pragma unroll
  for (int j = 4; j < 16; j++) {
    a0[j & 3] = fmaxf(a0[j & 3], fmaxf(s[4 * j], s[4 * j + 1])); a1[j & 3] = fmaxf(a1[j & 3], fmaxf(s[4 * j + 2], s[4 * j + 3]));
  }
  mx0 = fmaxf(fmaxf(a0[0], a0[1]), fmaxf(a0[2], a0[3])); mx1 = fmaxf(fmaxf(a1[0], a1[1]), fmaxf(a1[2], a1[3]));
  mx0 = fmaxf(mx0, __shfl_xor_sync(0xffffffffu, mx0, 1)); mx1 = fmaxf(mx1, __shfl_xor_sync(0xffffffffu, mx1, 1));
  mx0 = fmaxf(mx0, __shfl_xor_sync(0xffffffffu, mx0, 2)); mx1 = fmaxf(mx1, __shfl_xor_sync(0xffffffffu, mx1, 2));
}
__device__ __forceinline__ void sm_set_ref(Softmax& st, float m0, float m1) {
  st.mc0 = m0 * SM_C; st.mc1 = m1 * SM_C;
  const float t0 = m0 + SM_TAU / SM_C, t1 = m1 + SM_TAU / SM_C;
  st.th0 = t0 >= 0.f ? __float_as_int(t0) : (int)0x80000000;
  st.th1 = t1 >= 0.f ? __float_as_int(t1) : (int)0x80000000;
}
__device__ __forceinline__ void sm_first(float (&s)[64], Softmax& st, int row_in_blk, int q) {
#pragma unroll
  for (int j = 0; j < 16; j++) {
    const int c = 8 * j + 2 * q;
    if (c > row_in_blk) s[4 * j] = -INFINITY;
    if (c + 1 > row_in_blk) s[4 * j + 1] = -INFINITY;
    if (c > row_in_blk + 8) s[4 * j + 2] = -INFINITY;
    if (c + 1 > row_in_blk + 8) s[4 * j + 3] = -INFINITY;
  }
  float mx0, mx1;
  row_max(s, mx0, mx1);
  sm_set_ref(st, mx0, mx1);
  st.m0 = mx0; st.m1 = mx1;
  st.l0 = 0.f; st.l1 = 0.f;
}
template<int J0>
__device__ __forceinline__ void sm_first_tri(float (&s)[64], Softmax& st, int rl, int q) {
#pragma unroll
  for (int j = 0; j < 8; j++) {
    const int c = 8 * j + 2 * q, o = 4 * (J0 + j);
    if (c > rl) s[o] = -INFINITY;
    if (c + 1 > rl) s[o + 1] = -INFINITY;
    if (c > rl + 8) s[o + 2] = -INFINITY;
    if (c + 1 > rl + 8) s[o + 3] = -INFINITY;
  }
  constexpr int NJ = J0 + 8;
  float a0[4], a1[4];
#pragma unroll
  for (int i = 0; i < 4; i++) { a0[i] = fmaxf(s[4 * i], s[4 * i + 1]); a1[i] = fmaxf(s[4 * i + 2], s[4 * i + 3]); }
#pragma unroll
  for (int j = 4; j < NJ; j++) {
    a0[j & 3] = fmaxf(a0[j & 3], fmaxf(s[4 * j], s[4 * j + 1])); a1[j & 3] = fmaxf(a1[j & 3], fmaxf(s[4 * j + 2], s[4 * j + 3]));
  }
  float mx0 = fmaxf(fmaxf(a0[0], a0[1]), fmaxf(a0[2], a0[3])), mx1 = fmaxf(fmaxf(a1[0], a1[1]), fmaxf(a1[2], a1[3]));
  mx0 = fmaxf(mx0, __shfl_xor_sync(0xffffffffu, mx0, 1)); mx1 = fmaxf(mx1, __shfl_xor_sync(0xffffffffu, mx1, 1));
  mx0 = fmaxf(mx0, __shfl_xor_sync(0xffffffffu, mx0, 2)); mx1 = fmaxf(mx1, __shfl_xor_sync(0xffffffffu, mx1, 2));
  sm_set_ref(st, mx0, mx1);
  st.m0 = mx0; st.m1 = mx1;
  st.l0 = 0.f; st.l1 = 0.f;
}
template<int NJ>
__device__ __forceinline__ void sm_sum_cvt_n(const float (&s)[64], uint32_t (&p)[32], Softmax& st) {
  float r0 = 0.f, r1 = 0.f, r2 = 0.f, r3 = 0.f;
#pragma unroll
  for (int j = 0; j < NJ; j++) { r0 += s[4 * j]; r1 += s[4 * j + 1]; r2 += s[4 * j + 2]; r3 += s[4 * j + 3]; }
  st.l0 += r0 + r1; st.l1 += r2 + r3;
#pragma unroll
  for (int i = 0; i < 32; i++) p[i] = i < 2 * NJ ? pack_bf16(s[2 * i], s[2 * i + 1]) : 0u;
}
__device__ __forceinline__ bool sm_next(float (&s)[64], Softmax& st, float& al0, float& al1) {
  int a[4];
#pragma unroll
  for (int i = 0; i < 4; i++) {
    const int o = (i >> 1) * 32 + (i & 1) * 2;
    a[i] = __vimax3_s32(__float_as_int(s[o]), __float_as_int(s[o + 1]), __float_as_int(s[o + 4]));
  }
#pragma unroll
  for (int i = 0; i < 4; i++) {
    const int o = (i >> 1) * 32 + (i & 1) * 2;
    a[i] = __vimax3_s32(a[i], __float_as_int(s[o + 5]), __float_as_int(s[o + 8]));
#pragma unroll
    for (int k = 2; k < 7; k++) a[i] = __vimax3_s32(a[i], __float_as_int(s[o + 4 * k + 1]), __float_as_int(s[o + 4 * k + 4]));
  }
  const int mx0 = __vimax3_s32(a[0], a[2], max(__float_as_int(s[29]), __float_as_int(s[61])));
  const int mx1 = __vimax3_s32(a[1], a[3], max(__float_as_int(s[31]), __float_as_int(s[63])));
  const bool bad = __any_sync(0xffffffffu, mx0 >= st.th0 || mx1 >= st.th1);
  if (bad) {
    float d0, d1;
    row_max(s, d0, d1);
    d0 = fmaxf(d0, st.m0); d1 = fmaxf(d1, st.m1);
    al0 = ex2((st.m0 - d0) * SM_C); al1 = ex2((st.m1 - d1) * SM_C);
    st.m0 = d0; st.m1 = d1;
    sm_set_ref(st, d0, d1);
    st.l0 *= al0; st.l1 *= al1;
  }
  return bad;
}
template<int J0, int J1>
__device__ __forceinline__ void sm_exp(float (&s)[64], const Softmax& st) {
  const float n0 = -st.mc0, n1 = -st.mc1;
#pragma unroll
  for (int j = J0; j < J1; j++) {
    s[4 * j] = ex2(fmaf(s[4 * j], SM_C, n0)); s[4 * j + 1] = ex2(fmaf(s[4 * j + 1], SM_C, n0));
    s[4 * j + 2] = ex2(fmaf(s[4 * j + 2], SM_C, n1)); s[4 * j + 3] = ex2(fmaf(s[4 * j + 3], SM_C, n1));
  }
}
__device__ __forceinline__ void sm_sum_cvt(const float (&s)[64], uint32_t (&p)[32], Softmax& st) {
  float r0 = 0.f, r1 = 0.f, r2 = 0.f, r3 = 0.f;
#pragma unroll
  for (int j = 0; j < 16; j++) { r0 += s[4 * j]; r1 += s[4 * j + 1]; r2 += s[4 * j + 2]; r3 += s[4 * j + 3]; }
  st.l0 += r0 + r1; st.l1 += r2 + r3;
#pragma unroll
  for (int i = 0; i < 32; i++) p[i] = pack_bf16(s[2 * i], s[2 * i + 1]);
}
__device__ __forceinline__ void issue_qk(float (&s)[64], const uint32_t (&qf)[32], uint32_t ks) {
  const uint32_t db = desc_lo(ks, 16);
#pragma unroll
  for (int kk = 0; kk < 8; kk++)
    wgmma_m64n128k16_rs<0>(s, qf[4 * kk], qf[4 * kk + 1], qf[4 * kk + 2], qf[4 * kk + 3], db + (kk >> 2) * 1024 + (kk & 3) * 2, kk != 0);
}
__device__ __forceinline__ void issue_qk_half(float (&s)[64], const uint32_t (&qf)[32], uint32_t ks) {
  const uint32_t db = desc_lo(ks, 16);
#pragma unroll
  for (int kk = 0; kk < 8; kk++)
    wgmma_m64n64k16_rs<0>(s, qf[4 * kk], qf[4 * kk + 1], qf[4 * kk + 2], qf[4 * kk + 3], db + (kk >> 2) * 1024 + (kk & 3) * 2, kk != 0);
}
__device__ __forceinline__ void issue_pv(float (&o)[64], const uint32_t (&p)[32], uint32_t vs, int accumulate) {
  const uint32_t db = desc_lo(vs, 16384);
#pragma unroll
  for (int kk = 0; kk < 8; kk++)
    wgmma_m64n128k16_rs<1>(o, p[4 * kk], p[4 * kk + 1], p[4 * kk + 2], p[4 * kk + 3], db + kk * 128, kk == 0 ? accumulate : 1);
}
template<int K0, int K1>
__device__ __forceinline__ void issue_pv_part(float (&o)[64], const uint32_t (&p)[32], uint32_t vs, int accumulate) {
  const uint32_t db = desc_lo(vs, 16384);
#pragma unroll
  for (int kk = K0; kk < K1; kk++)
    wgmma_m64n128k16_rs<1>(o, p[4 * kk], p[4 * kk + 1], p[4 * kk + 2], p[4 * kk + 3], db + kk * 128, kk == 0 ? accumulate : 1);
}
template<int K0>
__device__ __forceinline__ void issue128(float (&d)[64], uint32_t slot, int wg, bool first) {
  const uint32_t da = desc_lo(slot + wg * 8192, 16), db = desc_lo(slot + 16384, 8192);
#pragma unroll
  for (int k = K0; k < 4; k++) wgmma_m64n128k16_ss<1>(d, da + k * 2, db + k * 128, !(first && k == K0));
}

__device__ __forceinline__ void issue128h(float (&d)[64], uint32_t slot, int wg) {
  const uint32_t da = desc_lo(slot + wg * 8192, 16), db = desc_lo(slot + 16384, 4096);
#pragma unroll
  for (int k = 0; k < 4; k++) wgmma_m64n128k16_ss<1>(d, da + k * 2, db + (k >> 1) * 512 + (k & 1) * 128, 1);
}

struct Maps { CUtensorMap ckv, wk, wv, wq, xn, kst, vst, kld, vld, ctxst, ctxld, wo, h, wg, wu, actst, actld, wd, act1st, act1ld, wd32, wq2, wg32, wu32; };
struct Ptrs { const __nv_bfloat16 *x, *wg, *wu, *wo, *wd, *ckv, *wk, *wv; __nv_bfloat16* out; };

constexpr uint32_t G_ST = 49152, S_ST = 32768;
constexpr uint32_t O_STG = 196608, O_CS = 229376, O_BAR = 231168;
constexpr uint32_t B_GF = O_BAR, B_GE = O_BAR + 32, B_SF = O_BAR + 64, B_SE = O_BAR + 112, B_TF = O_BAR + 160, B_TE = O_BAR + 176,
                   B_XR = O_BAR + 192, B_XF = O_BAR + 208, B_CS = O_BAR + 224, B_PB = O_BAR + 232, B_CS2 = O_BAR + 240;
constexpr int MK_SMEM = 232448;

__device__ __forceinline__ int attn_qblock(int h, int r, int t) {
  return t == 0 ? 15 - r : (t == 1 ? 8 + r : (((t == 2) == ((h & 1) != 0)) ? r : 7 - r));
}

__global__ void __cluster_dims__(2, 1, 1) __launch_bounds__(384, 1)
k_mega(const __grid_constant__ Maps maps, const __grid_constant__ Ptrs ptrs) {
  extern __shared__ __align__(1024) uint8_t smem_raw[];
  const uint32_t sb = smem_u32(smem_raw);
  const int wg = __shfl_sync(0xffffffffu, threadIdx.x >> 7, 0);
  const int b = blockIdx.x, h = b >> 2, r = b & 3, rho = b & 1;
  const int tm = b >> 3, tn = (b >> 1) & 3;
#define CE(i)
  CE(0);
  if (wg == 2) {
    reg_dealloc<40>();
    if (threadIdx.x == 256) {
      prefetch_3d(rho ? &maps.wv : &maps.wk, 0, 0, h * 2); prefetch_3d(rho ? &maps.wv : &maps.wk, 0, 64, h * 2);
      CE(1);
      for (int s = 0; s < 4; s++) { mbar_init(sb + B_GF + 8 * s, 1); mbar_init(sb + B_GE + 8 * s, 16); }
      for (int s = 0; s < 6; s++) { mbar_init(sb + B_SF + 8 * s, 1); mbar_init(sb + B_SE + 8 * s, 8); }
      for (int s = 0; s < 2; s++) {
        mbar_init(sb + B_TF + 8 * s, 4); mbar_init(sb + B_TE + 8 * s, 1); mbar_init(sb + B_XR + 8 * s, 1); mbar_init(sb + B_XF + 8 * s, 1);
      }
      mbar_init(sb + B_CS, 1); mbar_init(sb + B_PB, 1); mbar_init(sb + B_CS2, 1);
      asm volatile("fence.mbarrier_init.release.cluster;" ::: "memory");
    }
    if (threadIdx.x == 352) { prefetch_2d(&maps.ckv, 0, (KV_GRP(0) * 4 + r) * 128); prefetch_2d(&maps.ckv, 64, (KV_GRP(0) * 4 + r) * 128); }
    __syncwarp();
    PROF_INIT();
    named_bar_sync(0, 384);
    asm volatile("barrier.cluster.arrive.relaxed.aligned;" ::: "memory");
    cluster_wait();
    if (threadIdx.x == 256) PROF_T(1, 27);
    const int warp = (threadIdx.x >> 5) & 3, lane = threadIdx.x & 31;
    if (warp == 0) {
      if (lane == 0) {
        PROF_G(0, 16);
        unsigned long long ticket;
        asm volatile("atom.global.add.u64 %0, [%1], 1;" : "=l"(ticket) : "l"(&g_ticket) : "memory");
        asm volatile("{\n.reg .u64 t;\nadd.u64 t, %0, 1;\nsub.u64 %0, t, 1;\n}" : "+l"(ticket) :: "memory");
        const uint64_t pF = pol_first();
        const uint64_t pN = EVN ? pol_normal() : pol_unch();
#define EVX (EVN | EVU)
#pragma unroll 1
        for (int f = 0; f < 32; f++) {
          const int st = f & 3, kb = f & 7, mb = KV_GRP(f >> 3) * 4 + r;
          const uint32_t bar = sb + B_GF + 8 * st, sa = sb + st * G_ST;
          mbar_wait<1>(sb + B_GE + 8 * st, ((f >> 2) & 1) ^ 1);
          mbar_expect_tx(bar, G_ST);
          if (EVX & 1) ld2(true, pN, sa, &maps.ckv, bar, kb * 64, mb * 128); else
          ld2(EVF & 1, pF, sa, &maps.ckv, bar, kb * 64, mb * 128);
          if (EVX & 2) ld3mc(true, pN, sa + 16384 + rho * 16384, rho ? &maps.wv : &maps.wk, bar, 0, kb * 64, h * 2); else
          ld3mc((EVF & 4) || ((EVF & 2) && f >= 24) || ((EVF & 2048) && f >= 16), pF, sa + 16384 + rho * 16384, rho ? &maps.wv : &maps.wk, bar, 0, kb * 64, h * 2);
          if (f == PFQ) {
            prefetch_3d(&maps.wq, 0, r * 128, h * 2); prefetch_3d(&maps.wq, 0, r * 128 + 64, h * 2);
          }
        }
        asm volatile("" : "+l"(ticket) :: "memory");
        const uint32_t ep1 = (uint32_t)(ticket >> 7) + 1;
        asm volatile("st.shared.u32 [%0], %1;" :: "r"(sb + B_CS2 + 8), "r"(ep1 * 8) : "memory");
        mbar_arrive(sb + B_CS2);
        int sl = 0; uint32_t ph = 1;
        auto s_acq = [&](uint32_t bytes) -> uint32_t {
          mbar_wait<2>(sb + B_SE + 8 * sl, ph);
          mbar_expect_tx(sb + B_SF + 8 * sl, bytes);
          return sb + sl * S_ST;
        };
        auto s_nxt = [&]() { if (++sl == 6) { sl = 0; ph ^= 1; } };
        auto s_throttle = [&](int n) { const int a = sl - n; mbar_wait<13>(sb + B_SF + 8 * (a < 0 ? a + 6 : a), a < 0 ? ph : ph ^ 1); };
        auto g_drain = [&](int d, uint32_t par) {
          if (d == 0) mbar_wait<3>(sb + B_GE, par);
          if (d == 1) mbar_wait<3>(sb + B_GE + 8, par);
          if (d == 3) mbar_wait<3>(sb + B_GE + 16, par);
          if (d == 4) mbar_wait<3>(sb + B_GE + 24, par);
        };
#pragma unroll 1
        for (int t = 0; t < 4; t++) {
          const int qb = attn_qblock(h, r, t);
          flag_wait<4>(&g_sync[(C_XN + qb) * 8], ep1 * 24);
          if (t == 0) PROF_T(1, 3);
#pragma unroll 1
          for (int kb = 0; kb < 8; kb++) {
            if (t == 0) g_drain(kb, 1);
            const uint32_t d = s_acq(S_ST), bar = sb + B_SF + 8 * sl;
            const int kr = kb;
            ld2((EVX & 4) || ((EVF & 32) && (t < 2 || qb > 3 || t == 3)), (EVX & 4) ? pN : pF, d, &maps.xn, bar, kr * 64, qb * 128);
            ld3((EVX & 8) || ((EVF & 4096) && t == 3), (EVX & 8) ? pN : pF, d + 16384, &maps.wq, bar, 0, kr * 64, h * 2);
            s_nxt();
          }
#define KV_EF ((EVF & 1024) || ((EVF & 64) && (t == 3 || blk >= (t == 0 ? 12 : (t == 1 ? 8 : 4)))) || ((EVF & 8192) && t == 3) || ((EVF & 16384) && t == 0 && blk >= 12))
          auto ld_kv = [&](const CUtensorMap* mp, int blk) {
            const uint32_t d = s_acq(S_ST);
            if (KV_EF) ld3(true, pF, d, mp, sb + B_SF + 8 * sl, 0, h * SEQ + blk * 128, 0);
            else ld3(EVX & 16, pN, d, mp, sb + B_SF + 8 * sl, 0, h * SEQ + blk * 128, 0);
            s_nxt();
          };
          auto kv_blk = [&](int j) { return (t == 0 && j < 12) ? T0_GRP(j >> 2) * 4 + (j & 3) : j; };
          if (t == 0) PROF_T(1, 4);
          if (t == 0) { mbar_wait<5>(sb + B_PB, 0); fence_async_global(); }
          if (t == 0) PROF_T(1, 5);
          ld_kv(&maps.kld, qb);
#pragma unroll 1
          for (int j = qb; j > 0; j--) {
            if (t == 0 && (j & 3) == 0) FLAG_WAIT<5>(&g_sync[(C_KV + h * 4 + 3 - T0_GRP((j >> 2) - 1)) * 8], ep1 * 8);
            ld_kv(&maps.kld, kv_blk(j - 1));
            ld_kv(&maps.vld, kv_blk(j));
          }
          ld_kv(&maps.vld, kv_blk(0));
          if (t == 3) { prefetch_l2(ptrs.wg + b * 4 * FF, 4 * FF * 2); prefetch_l2(ptrs.wu + b * 4 * FF, 4 * FF * 2); }
          if (t == 2) { prefetch_l2(ptrs.wo + b * 32 * DM, 32 * DM * 2); prefetch_l2(ptrs.x + b * 16 * DM, 16 * DM * 2); }
        }
        const int fg = tn * 2 + rho;
        {
          const int c1 = tm < 4 ? 1 : 0;
          int npre = 0;
#pragma unroll 1
          for (int kb = 0; kb < 32; kb++) {
            const int cls = (kb >> 4) ^ c1;
            const int k0 = (16 * rho + ((kb >> 1) & 7) * 2 + cls) * 128 + (kb & 1) * 64;
            if ((kb & 15) == 0) {
              PROF_T(1, 6 + (kb >> 4) * 2);
              const uint32_t* flag = &g_sync[(C_CTX + (tm * 2 + rho) * 2 + cls) * 8];
              int s2 = sl; uint32_t p2 = ph; bool ok = false;
#pragma unroll 1
              for (int it = 0; it < 256 && npre < 6; it++) {
                ok = flag_test(flag, ep1 * 16);
                if (ok) break;
#pragma unroll 1
                while (npre < 6 && mbar_test(sb + B_SE + 8 * s2, p2)) {
                  mbar_expect_only(sb + B_SF + 8 * s2, 16384);
                  tma_load_3d(sb + s2 * S_ST + 16384, &maps.wo, sb + B_SF + 8 * s2, 0, k0 + (npre >> 1) * 256 + (npre & 1) * 64, tn * 2);
                  npre++;
                  if (++s2 == 6) { s2 = 0; p2 ^= 1; }
                }
              }
              if (ok) fence_async_global(); else
              FLAG_WAIT<7>(flag, ep1 * 16);
              PROF_T(1, 7 + (kb >> 4) * 2);
            }
            if (kb == 8) {
              flag_wait<6>(&g_sync[C_CS * 8], ep1 * 128);
              mbar_expect_tx(sb + B_CS, 1792);
              bulk_load(sb + O_CS, g_cs + fg * 224, 896, sb + B_CS);
              bulk_load(sb + O_CS + 896, g_cs + FF + fg * 224, 896, sb + B_CS);
              prefetch_l2(ptrs.wd + b * 14 * DM, 14 * DM * 2);
            }
            const uint32_t d = sb + sl * S_ST, bar = sb + B_SF + 8 * sl;
            if (npre > 0) { mbar_expect_tx(bar, 16384); npre--; }
            else { s_acq(S_ST); tma_load_3d(d + 16384, &maps.wo, bar, 0, k0, tn * 2); }
            tma_load_2d(d, &maps.ctxld, bar, k0, tm * 128);
            s_nxt();
          }
        }
        PROF_T(1, 0);
        {
          const uint32_t* hflag = &g_sync[(C_H + tm) * 8];
          const uint32_t inv = (ep1 & 1) ? 0u : 0xFFFFu;
          uint32_t todo = 0x5555u & ~(1u << (2 * fg)), rdy = 0;
#pragma unroll 1
          for (int f = 0; f < 8; f++) {
            const int st = f & 3, x0 = fg * 224;
            const uint32_t bar = sb + B_GF + 8 * st, sa = sb + st * G_ST;
            mbar_wait<8>(sb + B_GE + 8 * st, (f >> 2) & 1);
            int kb = fg;
            if (f > 0) {
              if ((rdy & todo) == 0) {
                if (f == 1) PROF_T(1, 10);
#pragma unroll 1
                for (int it = 0; (rdy & todo) == 0; it++) {
                  const uint32_t v = ld_acquire_u32(hflag) ^ inv;
                  rdy = v & (v >> 1);
                  if (it > 2000000) asm volatile("trap;");
                }
                fence_async_global();
                if (f == 1) PROF_T(1, 11);
              }
              kb = (__ffs(rdy & todo) - 1) >> 1;
              todo &= ~(1u << (2 * kb));
            }
            mbar_expect_tx(bar, f == 0 ? 32768 : 49152);
            if (f > 0) { tma_load_2d(sa, &maps.h, bar, kb * 64, tm * 128); tma_load_2d(sa + 8192, &maps.h, bar, kb * 64, tm * 128 + 64); }
            tma_load_2d(sa + 16384, &maps.wg, bar, x0, kb * 64);
            tma_load_2d(sa + 24576, &maps.wg, bar, x0 + 64, kb * 64);
            tma_load_2d(sa + 32768, &maps.wu, bar, x0, kb * 64);
            tma_load_2d(sa + 40960, &maps.wu, bar, x0 + 64, kb * 64);
          }
#pragma unroll 1
          for (int f = 8; f < 16; f++) {
            const int st = f & 3, kb = f & 7;
            const uint32_t bar = sb + B_GF + 8 * st, sa = sb + st * G_ST;
            mbar_wait<8>(sb + B_GE + 8 * st, (f >> 2) & 1);
            mbar_expect_tx(bar, 24576 + 16384);
            tma_load_2d_mc(sa + rho * 8192, &maps.h, bar, kb * 64, tm * 128 + rho * 64);
            tma_load_3d(sa + 16384, &maps.wg32, bar, 0, kb * 64, fg * 7 + 4);
            tma_load_3d(sa + 28672, &maps.wu32, bar, 0, kb * 64, fg * 7 + 4);
          }
        }
        PROF_T(1, 1);
#pragma unroll 1
        for (int d = 0; d < 8; d++) {
          if (d < 6) g_drain(d, 0);
          if (d == 0) { PROF_T(1, 12); FLAG_WAIT<10>(&g_sync[(C_ACT + (tm * 2 + rho) * 2) * 8], ep1 * 8); PROF_T(1, 13); }
          const int k0 = (4 * rho + (d >> 1)) * 224 + (d & 1) * 64;
          const uint32_t dd = s_acq(S_ST), bar = sb + B_SF + 8 * sl;
          tma_load_3d(dd + 16384, &maps.wd, bar, 0, k0, tn * 2);
          tma_load_2d(dd, &maps.actld, bar, k0, tm * 128);
          s_nxt();
        }
        {
          auto ld_wd = [&](int j, int s2) {
#pragma unroll
            for (int e = 0; e < 2; e++) {
              const int u = 2 * j + e, g = (u * 11) >> 5;
              tma_load_3d(sb + s2 * S_ST + 16384 + e * 8192, &maps.wd32, sb + B_SF + 8 * s2, 0, (4 * rho + g) * 224 + 128 + (u - 3 * g) * 32, tn * 2);
            }
          };
          PROF_T(1, 14);
          const uint32_t* flag = &g_sync[(C_ACT + (tm * 2 + rho) * 2 + 1) * 8];
          int npre = 0;
          int s2 = sl; uint32_t p2 = ph; bool ok = false;
#pragma unroll 1
          for (int it = 0; it < 256 && npre < 6; it++) {
            ok = flag_test(flag, ep1 * 8);
            if (ok) break;
#pragma unroll 1
            while (npre < 6 && mbar_test(sb + B_SE + 8 * s2, p2)) {
              mbar_expect_only(sb + B_SF + 8 * s2, 16384);
              ld_wd(npre, s2);
              npre++;
              if (++s2 == 6) { s2 = 0; p2 ^= 1; }
            }
          }
          if (ok) fence_async_global(); else
          FLAG_WAIT<10>(flag, ep1 * 8);
          PROF_T(1, 15);
#pragma unroll 1
          for (int j = 0; j < 6; j++) {
            const uint32_t bar = sb + B_SF + 8 * sl;
            if (j < npre) mbar_expect_tx(bar, 16384);
            else { s_acq(S_ST); ld_wd(j, sl); }
            tma_load_2d(sb + sl * S_ST, &maps.act1ld, bar, rho * 384 + j * 64, tm * 128);
            s_nxt();
          }
        }
        PROF_T(1, 2);
      }
    } else {
#pragma unroll 1
      for (int i = warp - 1; i < 16; i += 3) {
        const int row = b * 16 + i;
        const uint4* src = reinterpret_cast<const uint4*>(ptrs.x + row * DM);

        const uint64_t pF = pol_first();
        const uint4 a = ldg_v4_h(src + lane, pF), c = ldg_v4_h(src + lane + 32, pF);
        uint32_t w[8] = {a.x, a.y, a.z, a.w, c.x, c.y, c.z, c.w};
        float s = 0.f;
#pragma unroll
        for (int k = 0; k < 8; k++) s += bf16lo(w[k]) + bf16hi(w[k]);
#pragma unroll
        for (int o = 16; o > 0; o >>= 1) s += __shfl_xor_sync(0xffffffffu, s, o);
        const float mean = s * (1.f / 512.f);
        float ss = 0.f;
#pragma unroll
        for (int k = 0; k < 8; k++) { const float u = bf16lo(w[k]) - mean, v = bf16hi(w[k]) - mean; ss += u * u + v * v; }
#pragma unroll
        for (int o = 16; o > 0; o >>= 1) ss += __shfl_xor_sync(0xffffffffu, ss, o);
        const float rstd = rsqrtf(ss * (1.f / 512.f) + 1e-5f);
#pragma unroll
        for (int k = 0; k < 8; k++) w[k] = pack_bf16((bf16lo(w[k]) - mean) * rstd, (bf16hi(w[k]) - mean) * rstd);
        uint4* dst = reinterpret_cast<uint4*>(g_xn + row * DM);
        dst[lane] = make_uint4(w[0], w[1], w[2], w[3]);
        dst[lane + 32] = make_uint4(w[4], w[5], w[6], w[7]);
      }
      __syncwarp();
      if (lane == 0) flag_arrive(&g_sync[(C_XN + (b >> 3)) * 8]);
      if (warp == 3) {
        if (lane == 0) {
          mbar_wait<12>(sb + B_CS2, 0);
          uint32_t kv_target;
          asm volatile("ld.shared.u32 %0, [%1];" : "=r"(kv_target) : "r"(sb + B_CS2 + 8) : "memory");
          flag_wait<5>(&g_sync[(C_KV + h * 4) * 8], kv_target);
          mbar_arrive(sb + B_PB);
        }
        __syncwarp();
        if (lane < 28) {
          const int cp = lane % 14, hf = lane / 14;
          const uint32_t* src = reinterpret_cast<const uint32_t*>((b < 64 ? ptrs.wg : ptrs.wu) + (size_t)hf * 256 * FF + (b & 63) * 28 + cp * 2);
          float s0 = 0.f, s1 = 0.f;
          const uint64_t pF = pol_first();
#pragma unroll 8
          for (int k = 0; k < 256; k++) { const uint32_t v = ldg_h(src + k * (FF / 2), pF); s0 += bf16lo(v); s1 += bf16hi(v); }
          const float t0 = __shfl_down_sync(0x0fffffffu, s0, 14), t1 = __shfl_down_sync(0x0fffffffu, s1, 14);
          if (lane < 14) *reinterpret_cast<float2*>(g_cs + b * 28 + cp * 2) = make_float2(s0 + t0, s1 + t1);
        }
        __syncwarp();
        if (lane == 0) flag_arrive(&g_sync[C_CS * 8]);
      } else if (lane == 0) {
        const int w = warp - 1;
        const uint32_t stg = sb + O_STG + w * 16384;
        const uint32_t xr_peer = mapa(sb + B_XR + 8 * w, rho ^ 1);
#pragma unroll 1
        for (int job = 0; job < 15; job++) {
          mbar_wait<11>(sb + B_TF + 8 * w, job & 1);
          if (w == 0) PROF_T(3, job);
          uint32_t* flag = nullptr;
          if (job < 8) {
            const int i = job >> 1;
            if (EVX & 64) tma_store_3d_h((job & 1) ? &maps.vst : &maps.kst, stg, 0, h * SEQ + ((3 - i) * 4 + r) * 128 + w * 64, 0, EVN ? pol_normal() : pol_unch());
            else
            tma_store_3d((job & 1) ? &maps.vst : &maps.kst, stg, 0, h * SEQ + (KV_GRP(i) * 4 + r) * 128 + w * 64, 0);
            if (job & 1) flag = &g_sync[(C_KV + h * 4 + 3 - KV_GRP(i)) * 8];
          } else if (job < 12) {
            const int qb = attn_qblock(h, r, job - 8);
            if (EVX & 128) tma_store_3d_h(&maps.ctxst, stg, 0, qb * 128 + w * 64, h * 2, EVN ? pol_normal() : pol_unch());
            else
            tma_store_3d(&maps.ctxst, stg, 0, qb * 128 + w * 64, h * 2);
            flag = &g_sync[(C_CTX + (qb * 2 + (h >> 4)) * 2 + (h & 1)) * 8];
          } else if (job == 12) {
            tma_store_2d(&maps.h, stg, tn * 128 + rho * 64, tm * 128 + w * 64);
            bulk_store(g_stats + (tm * 8 + tn * 2 + rho) * 128 + w * 64, stg + 8192, 512);
            flag = &g_sync[(C_H + tm) * 8];
          } else {
            const CUtensorMap* am = job == 13 ? &maps.actst : &maps.act1st;
            const int x0 = (tn * 2 + rho) * (job == 13 ? 224 : 96);
            tma_store_2d(am, stg, x0, tm * 128 + w * 64);
            tma_store_2d(am, stg + 8192, x0 + (job == 13 ? 64 : 32), tm * 128 + w * 64);
            flag = &g_sync[(C_ACT + (tm * 2 + (tn >> 1)) * 2 + (job - 13)) * 8];
          }
          bulk_commit();
          bulk_wait_read();
          if (w == 0) PROF_T(4, job);
          mbar_arrive(sb + B_TE + 8 * w);
          if (job == 11 || job == 14) mbar_arrive_cl(xr_peer);
          if (flag) {
            bulk_wait_all(); if (w == 0) PROF_T(5, job);
            const int cls = job < 8 ? 1 : (job < 12 ? 2 : (4 << (job - 12)));
            if (PUBM & cls) {
              if (PUB & 2) asm volatile("fence.proxy.async;" ::: "memory");
              if (PUB & 4) asm volatile("fence.proxy.async.global;" ::: "memory");
              if (job == 12) asm volatile("red.release.gpu.global.xor.b32 [%0], %1;" :: "l"(flag), "r"(1u << (2 * (tn * 2 + rho) + w)) : "memory");
              else if (PUB & 1) flag_arrive(flag); else flag_arrive_relaxed(flag);
            } else flag_arrive_relaxed(flag);
          }
          if (w == 0) PROF_T(2, job);
        }
      }
    }
    __syncwarp();
    PROF_DUMP();
    asm volatile("barrier.cluster.arrive.relaxed.aligned;" ::: "memory");
    asm volatile("barrier.cluster.wait.aligned;" ::: "memory");
  } else {
    reg_alloc<232>();
    const int lane = threadIdx.x & 31, warp = (threadIdx.x >> 5) & 3, q = lane & 3;
    const int row_in_blk = wg * 64 + warp * 16 + (lane >> 2);
    const uint32_t stg = sb + O_STG + wg * 16384;
    const uint32_t stm = stg + (warp * 16 + (lane & 7) + ((lane >> 3) & 1) * 8) * 128 + (((lane >> 4) ^ (lane & 7)) << 4);
    const uint32_t ge_cl = mapa(sb + B_GE, (lane & 1) ^ rho);
    auto g_release = [&](int st) { if (lane < 2) mbar_arrive_cl(ge_cl + 8 * st); };
    uint32_t jpar = 1;
    auto stg_acquire = [&]() { mbar_wait<20>(sb + B_TE + 8 * wg, jpar); jpar ^= 1; };
    auto stg_publish = [&]() { fence_async_smem(); __syncwarp(); if (lane == 0) mbar_arrive(sb + B_TF + 8 * wg); };
    auto stg_put = [&](int atom, int jp, uint32_t a, uint32_t c, uint32_t d, uint32_t e) {
      stmatrix_x4((stm + atom * 8192) ^ (((2 * jp) & 7) << 4), a, c, d, e);
    };
    CE(1);
    PROF_INIT();
    named_bar_sync(0, 384);
    asm volatile("barrier.cluster.arrive.relaxed.aligned;" ::: "memory");
    cluster_wait();
    if (threadIdx.x == 0) PROF_0(0);

    int sl = 0; uint32_t ph = 0;
    auto s_nxt = [&]() { if (++sl == 6) { sl = 0; ph ^= 1; } };
    auto s_release = [&](int a) { if (lane == 0) mbar_arrive(sb + B_SE + 8 * a); };
    float s[64];
    uint32_t qf[32];
    {
      float acc[128];
      uint32_t pk[64];
      auto put_tile = [&](int half) {
        stg_acquire();
#pragma unroll
        for (int jp = 0; jp < 8; jp++)
          stg_put(jp >> 2, jp, pk[half * 32 + 4 * jp], pk[half * 32 + 4 * jp + 1], pk[half * 32 + 4 * jp + 2], pk[half * 32 + 4 * jp + 3]);
        stg_publish();
      };
#pragma unroll
      for (int i = 0; i < 64; i++) pk[i] = 0;
      for (int i = 0; i < 4; i++) {
#pragma unroll
        for (int kb = 0; kb < 8; kb++) {
          const int st = kb & 3;
          mbar_wait<21>(sb + B_GF + 8 * st, (kb >> 2) & 1);
          const uint32_t da = desc_lo(sb + st * G_ST + wg * 8192, 16), db = desc_lo(sb + st * G_ST + 16384, 8192);
          wgmma_fence();
#pragma unroll
          for (int k = 0; k < 4; k++) wgmma_m64n256k16_ss<1>(acc, da + k * 2, db + k * 128, (kb | k) != 0);
          wgmma_commit();
          if (kb > 0) { wgmma_wait<1>(); g_release((kb - 1) & 3); }
          if (kb == 0 && i > 0) put_tile(0);
          if (kb == 4 && i > 0) put_tile(1);
        }
        wgmma_wait<0>();
        g_release(3);
        fence_regs(acc);
#pragma unroll
        for (int k = 0; k < 64; k++) pk[k] = pack_bf16(acc[2 * k], acc[2 * k + 1]);
        if (threadIdx.x == 0) PROF_0(1 + i);
      }
      int prev = 0;
#pragma unroll
      for (int kb = 0; kb < 8; kb++) {
        mbar_wait<22>(sb + B_SF + 8 * sl, ph);
        wgmma_fence();
        issue128<0>(s, sb + sl * S_ST, wg, kb == 0);
        wgmma_commit();
        if (kb > 0) { wgmma_wait<1>(); s_release(prev); }
        prev = sl; s_nxt();
        if (kb == 0) put_tile(0);
        if (kb == 4) put_tile(1);
      }
      wgmma_wait<0>();
      fence_regs(s);
      s_release(prev);
#pragma unroll
      for (int k = 0; k < 32; k++) qf[k] = pack_bf16(s[2 * k], s[2 * k + 1]);
    }
    if (threadIdx.x == 0) PROF_0(5);
    {
      float o[64]; uint32_t p[32];
      Softmax st; float al0 = 1.f, al1 = 1.f;
#pragma unroll
      for (int i = 0; i < 64; i++) o[i] = 0.f;
      if (wg == 1) named_bar_arrive(1, 256);
      for (int t = 0; t < 4; t++) {
        const int qb = attn_qblock(h, r, t);
        if (threadIdx.x == 0) PROF_T(6, t);
        mbar_wait<23>(sb + B_SF + 8 * sl, ph);
        if (threadIdx.x == 0) PROF_T(6, 4 + t);
        if (wg == 0) {
          named_bar_sync(1, 256);
          wgmma_fence();
          issue_qk_half(s, qf, sb + sl * S_ST);
          wgmma_commit();
          named_bar_arrive(2, 256);
          wgmma_wait<0>(); fence_regs(s);
          s_release(sl); s_nxt();
          sm_first_tri<0>(s, st, row_in_blk, q);
          sm_exp<0, 8>(s, st);
          sm_sum_cvt_n<8>(s, p, st);
        } else {
          named_bar_sync(2, 256);
          wgmma_fence();
          issue_qk(s, qf, sb + sl * S_ST);
          wgmma_commit();
          named_bar_arrive(1, 256);
          wgmma_wait<0>(); fence_regs(s);
          s_release(sl); s_nxt();
          sm_first_tri<8>(s, st, row_in_blk - 64, q);
          sm_exp<0, 16>(s, st);
          sm_sum_cvt_n<16>(s, p, st);
        }
        mbar_wait<24>(sb + B_SF + 8 * sl, ph);
        if (threadIdx.x == 0) PROF_T(6, 8 + t);
        for (int j = qb; j > 0; j--) {
          const int ks = sl; s_nxt();
          const int vs = sl;
          named_bar_sync(1 + wg, 256);
          wgmma_fence();
          issue_qk(s, qf, sb + ks * S_ST);
          wgmma_commit();
          mbar_wait<25>(sb + B_SF + 8 * vs, ph);
          s_nxt();
          wgmma_fence();
          issue_pv(o, p, sb + vs * S_ST, j != qb);
          wgmma_commit();
          named_bar_arrive(2 - wg, 256);
          wgmma_wait<1>(); fence_regs(s);
          s_release(ks);
          const bool bad = sm_next(s, st, al0, al1);
          sm_exp<0, 4>(s, st);
          fence_regs(s);
          mbar_wait<26>(sb + B_SF + 8 * sl, ph);
          wgmma_wait<0>(); fence_regs(o); fence_regs(p);
          s_release(vs);
          if (bad) {
#pragma unroll
            for (int i = 0; i < 16; i++) { o[4 * i] *= al0; o[4 * i + 1] *= al0; o[4 * i + 2] *= al1; o[4 * i + 3] *= al1; }
          }
          sm_exp<4, 16>(s, st);
          sm_sum_cvt(s, p, st);
        }
        if (threadIdx.x == 0) PROF_0(6 + t);
        const int vs = sl; s_nxt();
        named_bar_sync(1 + wg, 256);
        wgmma_fence();
        issue_pv(o, p, sb + vs * S_ST, qb != 0);
        wgmma_commit();
        if (t < 3 || wg == 0) named_bar_arrive(2 - wg, 256);
        float l0 = st.l0, l1 = st.l1;
        const int nkb = t < 3 ? 8 : 32;
        mbar_wait<27>(sb + B_SF + 8 * sl, ph);
        wgmma_fence();
        issue128<0>(s, sb + sl * S_ST, wg, true);
        wgmma_commit();
        int prev = sl; s_nxt();
        l0 += __shfl_xor_sync(0xffffffffu, l0, 1); l1 += __shfl_xor_sync(0xffffffffu, l1, 1);
        l0 += __shfl_xor_sync(0xffffffffu, l0, 2); l1 += __shfl_xor_sync(0xffffffffu, l1, 2);
        const float i0 = 1.f / l0, i1 = 1.f / l1;
        wgmma_wait<1>(); fence_regs(o); fence_regs(p);
        s_release(vs);
        auto put_ctx = [&](int jp) {
          stg_put(jp >> 2, jp, pack_bf16(o[8 * jp] * i0, o[8 * jp + 1] * i0), pack_bf16(o[8 * jp + 2] * i1, o[8 * jp + 3] * i1),
                  pack_bf16(o[8 * jp + 4] * i0, o[8 * jp + 5] * i0), pack_bf16(o[8 * jp + 6] * i1, o[8 * jp + 7] * i1));
        };
        stg_acquire();
        put_ctx(0); put_ctx(1);
        mbar_wait<28>(sb + B_SF + 8 * sl, ph);
        wgmma_fence();
        issue128<0>(s, sb + sl * S_ST, wg, false);
        wgmma_commit();
        put_ctx(2); put_ctx(3); put_ctx(4);
        wgmma_wait<1>(); s_release(prev); prev = sl; s_nxt();
        mbar_wait<28>(sb + B_SF + 8 * sl, ph);
        wgmma_fence();
        issue128<0>(s, sb + sl * S_ST, wg, false);
        wgmma_commit();
        put_ctx(5); put_ctx(6); put_ctx(7);
        stg_publish();
        wgmma_wait<1>(); s_release(prev); prev = sl; s_nxt();
        for (int kb = 3; kb < nkb; kb++) {
          mbar_wait<29>(sb + B_SF + 8 * sl, ph);
          wgmma_fence();
          issue128<0>(s, sb + sl * S_ST, wg, false);
          wgmma_commit();
          wgmma_wait<1>(); s_release(prev); prev = sl; s_nxt();
        }
        wgmma_wait<0>();
        fence_regs(s);
        s_release(prev);
#pragma unroll
        for (int k = 0; k < 32; k++) qf[k] = pack_bf16(s[2 * k], s[2 * k + 1]);
      }
    }
    if (threadIdx.x == 0) PROF_0(10);
#pragma unroll
    for (int st = 0; st < 4; st++) g_release(st);
    uint32_t xr[16];
    {
      const uint32_t* xs = reinterpret_cast<const uint32_t*>(ptrs.x + (tm * 128 + row_in_blk) * DM + tn * 128 + rho * 64 + 2 * q);
#pragma unroll
      for (int j = 0; j < 8; j++) { xr[2 * j] = __ldg(xs + 4 * j); xr[2 * j + 1] = __ldg(xs + 8 * (DM / 2) + 4 * j); }
    }

    const uint32_t xbuf = stg + (threadIdx.x & 127) * 16;
    const uint32_t xbuf_peer = mapa(xbuf, rho ^ 1), xf_peer = mapa(sb + B_XF + 8 * wg, rho ^ 1);
    auto exchange = [&](float (&d)[64], float (&v)[32], uint32_t par) {
      if ((threadIdx.x & 127) == 0) mbar_expect_tx(sb + B_XF + 8 * wg, 16384);
      mbar_wait_cl<30>(sb + B_XR + 8 * wg, par);
      if (threadIdx.x == 0) PROF_T(7, 8 + par * 16);
#pragma unroll
      for (int i = 0; i < 8; i++)
        st_async_v4(xbuf_peer + i * 2048, rho ? d[4 * i] : d[32 + 4 * i], rho ? d[4 * i + 1] : d[33 + 4 * i],
                    rho ? d[4 * i + 2] : d[34 + 4 * i], rho ? d[4 * i + 3] : d[35 + 4 * i], xf_peer);
#pragma unroll
      for (int i = 0; i < 32; i++) v[i] = rho ? d[32 + i] : d[i];
    };
    auto exchange_finish = [&](float (&v)[32], uint32_t par) {
      if (threadIdx.x == 0) PROF_T(7, 9 + par * 16);
      mbar_wait_cl<31>(sb + B_XF + 8 * wg, par);
      if (threadIdx.x == 0) PROF_T(7, 10 + par * 16);
#pragma unroll
      for (int i = 0; i < 8; i++) {
        const float4 u = lds_v4(xbuf + i * 2048);
        v[4 * i] += u.x; v[4 * i + 1] += u.y; v[4 * i + 2] += u.z; v[4 * i + 3] += u.w;
      }
    };
    {
      float v[32];
      exchange(s, v, 0);
      stg_acquire();
      exchange_finish(v, 0);
      uint32_t hp[16];
      float s0 = 0.f, s1 = 0.f;
#pragma unroll
      for (int j = 0; j < 8; j++) {
        hp[2 * j] = pack_bf16(bf16lo(xr[2 * j]) + v[4 * j], bf16hi(xr[2 * j]) + v[4 * j + 1]);
        hp[2 * j + 1] = pack_bf16(bf16lo(xr[2 * j + 1]) + v[4 * j + 2], bf16hi(xr[2 * j + 1]) + v[4 * j + 3]);
        s0 += bf16lo(hp[2 * j]) + bf16hi(hp[2 * j]); s1 += bf16lo(hp[2 * j + 1]) + bf16hi(hp[2 * j + 1]);
      }
      if (threadIdx.x == 0) PROF_T(7, 11);
      named_bar_sync(3 + wg, 128);
      if (threadIdx.x == 0) PROF_T(7, 12);
#pragma unroll
      for (int jp = 0; jp < 4; jp++) stg_put(0, jp, hp[4 * jp], hp[4 * jp + 1], hp[4 * jp + 2], hp[4 * jp + 3]);
      s0 += __shfl_xor_sync(0xffffffffu, s0, 1); s1 += __shfl_xor_sync(0xffffffffu, s1, 1);
      s0 += __shfl_xor_sync(0xffffffffu, s0, 2); s1 += __shfl_xor_sync(0xffffffffu, s1, 2);
      s0 *= (1.f / 64.f); s1 *= (1.f / 64.f);
      float m0 = 0.f, m1 = 0.f;
#pragma unroll
      for (int j = 0; j < 8; j++) {
        const float a = bf16lo(hp[2 * j]) - s0, c = bf16hi(hp[2 * j]) - s0, d = bf16lo(hp[2 * j + 1]) - s1, e = bf16hi(hp[2 * j + 1]) - s1;
        m0 += a * a + c * c; m1 += d * d + e * e;
      }
      m0 += __shfl_xor_sync(0xffffffffu, m0, 1); m1 += __shfl_xor_sync(0xffffffffu, m1, 1);
      m0 += __shfl_xor_sync(0xffffffffu, m0, 2); m1 += __shfl_xor_sync(0xffffffffu, m1, 2);
      if (q == 0) {
        const uint32_t a = stg + 8192 + (warp * 16 + (lane >> 2)) * 8;
        sts_v2(a, s0, m0); sts_v2(a + 64, s1, m1);
      }
      if (threadIdx.x == 0) PROF_T(7, 13);
      stg_publish();
    }
    if (threadIdx.x == 0) PROF_0(11);
    {
      float mu0, mu1, rs0, rs1;
      const uint32_t csb = sb + O_CS + q * 8;
      auto glu2 = [&](float g0, float g1, float u0, float u1, float2 cg, float2 cu, float nmu, float hrs) -> uint32_t {
        const float t0 = tanh_approx(hrs * fmaf(nmu, cg.x, g0)), t1 = tanh_approx(hrs * fmaf(nmu, cg.y, g1));
        const float w0 = fmaf(nmu, cu.x, u0), w1 = fmaf(nmu, cu.y, u1);
        return pack_bf16(hrs * fmaf(t0, w0, w0), hrs * fmaf(t1, w1, w1));
      };
      {
        float acc[128];
#pragma unroll
        for (int kb = 0; kb < 8; kb++) {
          const int st = kb & 3;
          mbar_wait<32>(sb + B_GF + 8 * st, (kb >> 2) & 1);
          if (kb == 0) named_bar_sync(3 + wg, 128);
          const uint32_t da = desc_lo(kb == 0 ? stg : sb + st * G_ST + wg * 8192, 16), db = desc_lo(sb + st * G_ST + 16384, 8192);
          wgmma_fence();
#pragma unroll
          for (int k = 0; k < 4; k++) wgmma_m64n256k16_ss<1>(acc, da + k * 2, db + k * 128, (kb | k) != 0);
          wgmma_commit();
          if (kb > 0) { wgmma_wait<1>(); g_release((kb - 1) & 3); }
          if (kb == 7) {
            const float2* sp = g_stats + (tm * 8 + 2 * q) * 128 + row_in_blk;
            const float2 a0 = ld_cg_f2(sp), a1 = ld_cg_f2(sp + 128), c0 = ld_cg_f2(sp + 8), c1 = ld_cg_f2(sp + 136);
            float t0 = a0.x + a1.x, t1 = c0.x + c1.x;
            t0 += __shfl_xor_sync(0xffffffffu, t0, 1); t1 += __shfl_xor_sync(0xffffffffu, t1, 1);
            t0 += __shfl_xor_sync(0xffffffffu, t0, 2); t1 += __shfl_xor_sync(0xffffffffu, t1, 2);
            mu0 = t0 * 0.125f; mu1 = t1 * 0.125f;
            float v0 = a0.y + a1.y + 64.f * ((a0.x - mu0) * (a0.x - mu0) + (a1.x - mu0) * (a1.x - mu0));
            float v1 = c0.y + c1.y + 64.f * ((c0.x - mu1) * (c0.x - mu1) + (c1.x - mu1) * (c1.x - mu1));
            v0 += __shfl_xor_sync(0xffffffffu, v0, 1); v1 += __shfl_xor_sync(0xffffffffu, v1, 1);
            v0 += __shfl_xor_sync(0xffffffffu, v0, 2); v1 += __shfl_xor_sync(0xffffffffu, v1, 2);
            rs0 = 0.5f * rsqrtf(v0 * (1.f / 512.f) + 1e-5f); rs1 = 0.5f * rsqrtf(v1 * (1.f / 512.f) + 1e-5f);
            mu0 = -mu0; mu1 = -mu1;
          }
        }
        wgmma_wait<0>();
        g_release(3);
        fence_regs(acc);
        mbar_wait<33>(sb + B_CS, 0);
        stg_acquire();
#pragma unroll
        for (int jp = 0; jp < 8; jp++) {
          const int j = 2 * jp;
          const float2 cg = lds_v2(csb + j * 32), cu = lds_v2(csb + 896 + j * 32);
          const float2 dg = lds_v2(csb + j * 32 + 32), du = lds_v2(csb + 896 + j * 32 + 32);
          stg_put(jp >> 2, jp, glu2(acc[4 * j], acc[4 * j + 1], acc[64 + 4 * j], acc[64 + 4 * j + 1], cg, cu, mu0, rs0),
                  glu2(acc[4 * j + 2], acc[4 * j + 3], acc[64 + 4 * j + 2], acc[64 + 4 * j + 3], cg, cu, mu1, rs1),
                  glu2(acc[4 * j + 4], acc[4 * j + 5], acc[64 + 4 * j + 4], acc[64 + 4 * j + 5], dg, du, mu0, rs0),
                  glu2(acc[4 * j + 6], acc[4 * j + 7], acc[64 + 4 * j + 6], acc[64 + 4 * j + 7], dg, du, mu1, rs1));
        }
      }
      if (threadIdx.x == 0) PROF_0(12);
      {
        float agu[96];
        float* const ag = agu; float* const au = agu + 48;
#pragma unroll
        for (int kb = 0; kb < 8; kb++) {
          const int st = kb & 3;
          mbar_wait<34>(sb + B_GF + 8 * st, (kb >> 2) & 1);
          const uint32_t da = desc_lo(sb + st * G_ST + wg * 8192, 16), db = desc_lo(sb + st * G_ST + 16384, 4096);
          wgmma_fence();
#pragma unroll
          for (int k = 0; k < 4; k++) wgmma_m64n192k16_ss64<1>(agu, da + k * 2, db + k * 64, (kb | k) != 0);
          wgmma_commit();
          if (kb == 0) stg_publish();
          if (kb > 0) { wgmma_wait<1>(); g_release((kb - 1) & 3); }
        }
        wgmma_wait<0>();
        g_release(3);
        fence_regs(agu);
        if (lane == 0) PROF_T(7, wg * 4 + warp);
        stg_acquire();
#pragma unroll
        for (int jp = 0; jp < 6; jp++) {
          const int j = 2 * jp;
          const float2 cg = lds_v2(csb + 512 + j * 32), cu = lds_v2(csb + 896 + 512 + j * 32);
          const float2 dg = lds_v2(csb + 512 + j * 32 + 32), du = lds_v2(csb + 896 + 512 + j * 32 + 32);
          const uint32_t a = glu2(ag[4 * j], ag[4 * j + 1], au[4 * j], au[4 * j + 1], cg, cu, mu0, rs0);
          const uint32_t c = glu2(ag[4 * j + 2], ag[4 * j + 3], au[4 * j + 2], au[4 * j + 3], cg, cu, mu1, rs1);
          const uint32_t d = glu2(ag[4 * j + 4], ag[4 * j + 5], au[4 * j + 4], au[4 * j + 5], dg, du, mu0, rs0);
          const uint32_t e = glu2(ag[4 * j + 6], ag[4 * j + 7], au[4 * j + 6], au[4 * j + 7], dg, du, mu1, rs1);
          if (jp < 4) stg_put(0, jp, a, c, d, e);
          if (jp >= 2) stg_put(1, jp - 2, a, c, d, e);
        }
        stg_publish();
      }
      if (threadIdx.x == 0) PROF_0(13);
      if (lane == 0) PROF_T(7, 16 + wg * 4 + warp);
      uint32_t hr[16];
      mbar_wait<35>(sb + B_SF + 8 * sl, ph);
      wgmma_fence();
      issue128<0>(s, sb + sl * S_ST, wg, true);
      wgmma_commit();
      int prev = sl; s_nxt();
#pragma unroll 1
      for (int kb = 1; kb < 8; kb++) {
        mbar_wait<35>(sb + B_SF + 8 * sl, ph);
        wgmma_fence();
        issue128<0>(s, sb + sl * S_ST, wg, false);
        wgmma_commit();
        wgmma_wait<1>(); s_release(prev);
        prev = sl; s_nxt();
      }
      {
        const uint32_t* hs = reinterpret_cast<const uint32_t*>(((ALIAS & 2) ? g_xn : g_h) + (tm * 128 + row_in_blk) * DM + tn * 128 + rho * 64 + 2 * q);
#pragma unroll
        for (int j = 0; j < 8; j++) { hr[2 * j] = ld_cg_u32(hs + 4 * j); hr[2 * j + 1] = ld_cg_u32(hs + 8 * (DM / 2) + 4 * j); }
      }
#pragma unroll 1
      for (int j = 0; j < 6; j++) {
        mbar_wait<36>(sb + B_SF + 8 * sl, ph);
        wgmma_fence();
        issue128h(s, sb + sl * S_ST, wg);
        wgmma_commit();
        wgmma_wait<1>(); s_release(prev); prev = sl; s_nxt();
      }
      wgmma_wait<0>();
      fence_regs(s);
      s_release(prev);
      if (threadIdx.x == 0) PROF_0(14);
      float v[32];
      exchange(s, v, 1);
      exchange_finish(v, 1);
      asm volatile("barrier.cluster.arrive.relaxed.aligned;" ::: "memory");
      uint32_t op[16];
#pragma unroll
      for (int j = 0; j < 8; j++) {
        op[2 * j] = pack_bf16(bf16lo(hr[2 * j]) + v[4 * j], bf16hi(hr[2 * j]) + v[4 * j + 1]);
        op[2 * j + 1] = pack_bf16(bf16lo(hr[2 * j + 1]) + v[4 * j + 2], bf16hi(hr[2 * j + 1]) + v[4 * j + 3]);
      }
      named_bar_sync(3 + wg, 128);
#pragma unroll
      for (int jp = 0; jp < 4; jp++) stg_put(0, jp, op[4 * jp], op[4 * jp + 1], op[4 * jp + 2], op[4 * jp + 3]);
      __syncwarp();
#pragma unroll
      for (int i = 0; i < 4; i++) {
        const int rr = warp * 16 + i * 4 + (lane >> 3);
        uint4 u;
        asm volatile("ld.shared.v4.u32 {%0, %1, %2, %3}, [%4];" : "=r"(u.x), "=r"(u.y), "=r"(u.z), "=r"(u.w) : "r"(stg + rr * 128 + (((lane ^ rr) & 7) << 4)) : "memory");
        *reinterpret_cast<uint4*>(ptrs.out + (tm * 128 + wg * 64 + rr) * DM + tn * 128 + rho * 64 + (lane & 7) * 8) = u;
      }
    }
    if (threadIdx.x == 0) { PROF_0(15); PROF_G(0, 17); }
    PROF_DUMP();
    asm volatile("barrier.cluster.wait.aligned;" ::: "memory");
  }
}

typedef CUresult (*PFN_encodeTiled_t)(CUtensorMap*, CUtensorMapDataType, cuuint32_t, void*, const cuuint64_t*, const cuuint64_t*,
                                      const cuuint32_t*, const cuuint32_t*, CUtensorMapInterleave, CUtensorMapSwizzle,
                                      CUtensorMapL2promotion, CUtensorMapFloatOOBfill);
static PFN_encodeTiled_t g_encode = nullptr;
static void make_map(CUtensorMap* m, const void* base, int rank, const cuuint64_t* dims, const cuuint64_t* strides, const cuuint32_t* box) {
  cuuint32_t es[5] = {1, 1, 1, 1, 1};
  g_encode(m, CU_TENSOR_MAP_DATA_TYPE_BFLOAT16, rank, const_cast<void*>(base), dims, strides, box, es, CU_TENSOR_MAP_INTERLEAVE_NONE,
           CU_TENSOR_MAP_SWIZZLE_128B, CU_TENSOR_MAP_L2_PROMOTION_L2_256B, CU_TENSOR_MAP_FLOAT_OOB_FILL_NONE);
}
static void map_2d(CUtensorMap* m, const void* base, int rows, int cols, int brows) {
  cuuint64_t d[2] = {(cuuint64_t)cols, (cuuint64_t)rows}, s[1] = {(cuuint64_t)cols * 2}; cuuint32_t b[2] = {64, (cuuint32_t)brows};
  make_map(m, base, 2, d, s, b);
}
static void map_2dp(CUtensorMap* m, const void* base, int rows, int cols, int pitch, int brows) {
  cuuint64_t d[2] = {(cuuint64_t)cols, (cuuint64_t)rows}, s[1] = {(cuuint64_t)pitch * 2}; cuuint32_t b[2] = {64, (cuuint32_t)brows};
  make_map(m, base, 2, d, s, b);
}
static void map_3d(CUtensorMap* m, const void* base, int rows, int cols, int brows) {
  cuuint64_t d[3] = {64, (cuuint64_t)rows, (cuuint64_t)(cols / 64)}, s[2] = {(cuuint64_t)cols * 2, 128}; cuuint32_t b[3] = {64, (cuuint32_t)brows, 2};
  make_map(m, base, 3, d, s, b);
}

static void map_3d32(CUtensorMap* m, const void* base, int rows, int cols) {
  cuuint64_t d[3] = {32, (cuuint64_t)rows, (cuuint64_t)(cols / 32)}, s[2] = {(cuuint64_t)cols * 2, 64}; cuuint32_t b[3] = {32, 64, 3}, es[3] = {1, 1, 1};
  g_encode(m, CU_TENSOR_MAP_DATA_TYPE_BFLOAT16, 3, const_cast<void*>(base), d, s, b, es, CU_TENSOR_MAP_INTERLEAVE_NONE,
           CU_TENSOR_MAP_SWIZZLE_64B, CU_TENSOR_MAP_L2_PROMOTION_L2_256B, CU_TENSOR_MAP_FLOAT_OOB_FILL_NONE);
}
static Maps g_maps;
static Ptrs g_ptrs;
static bool g_init = false;
static void* g_last_in[10];

extern "C" void kernel_launch(void* const* d_in, const int* in_sizes, int n_in, void* d_out, int out_size) {
  bool same = g_init;
  for (int i = 0; i < 10; i++) same = same && g_last_in[i] == d_in[i];
  if (!same) {
    for (int i = 0; i < 10; i++) g_last_in[i] = d_in[i];
    void* p = nullptr; cudaDriverEntryPointQueryResult qr;
    cudaGetDriverEntryPoint("cuTensorMapEncodeTiled", &p, cudaEnableDefault, &qr);
    g_encode = (PFN_encodeTiled_t)p;
    void *xn, *kk, *vv, *ctx, *hh, *act, *act1;
    cudaGetSymbolAddress(&xn, g_xn); cudaGetSymbolAddress(&kk, g_k); cudaGetSymbolAddress(&vv, g_v);
    cudaGetSymbolAddress(&ctx, g_ctx); cudaGetSymbolAddress(&hh, g_h); cudaGetSymbolAddress(&act, g_act); cudaGetSymbolAddress(&act1, g_act1);
    map_2d(&g_maps.ckv, d_in[1], SEQ, DM, 128);
    map_3d(&g_maps.wq, d_in[2], DM, HDALL, 64); map_3d(&g_maps.wk, d_in[3], DM, HDALL, 64); map_3d(&g_maps.wv, d_in[4], DM, HDALL, 64);
    map_2d(&g_maps.xn, xn, SEQ, DM, 128); map_2d(&g_maps.wq2, d_in[2], DM, HDALL, 64);
    map_3d(&g_maps.kst, kk, NH * SEQ, HD, 64); map_3d(&g_maps.vst, vv, NH * SEQ, HD, 64);
    map_3d(&g_maps.kld, kk, NH * SEQ, HD, 128); map_3d(&g_maps.vld, vv, NH * SEQ, HD, 128);
    map_3d(&g_maps.ctxst, ctx, SEQ, HDALL, 64); map_2d(&g_maps.ctxld, ctx, SEQ, HDALL, 128);
    map_3d(&g_maps.wo, d_in[5], HDALL, DM, 64);
    map_2d(&g_maps.h, hh, SEQ, DM, 64);
    map_2d(&g_maps.wg, d_in[7], DM, FF, 64); map_2d(&g_maps.wu, d_in[8], DM, FF, 64);
    map_3d32(&g_maps.wg32, d_in[7], DM, FF); map_3d32(&g_maps.wu32, d_in[8], DM, FF);
    map_2d(&g_maps.actst, act, SEQ, FF, 64); map_2d(&g_maps.actld, act, SEQ, FF, 128);
    map_3d(&g_maps.wd, d_in[9], FF, DM, 64); map_3d(&g_maps.wd32, d_in[9], FF, DM, 32);
    map_2d(&g_maps.act1st, act1, SEQ, 768, 64); map_2d(&g_maps.act1ld, act1, SEQ, 768, 128);
    map_2dp(&g_maps.actst, ctx, SEQ, FF, HDALL, 64); map_2dp(&g_maps.actld, ctx, SEQ, FF, HDALL, 128);
    map_2dp(&g_maps.act1st, (__nv_bfloat16*)ctx + 2048, SEQ, 768, HDALL, 64); map_2dp(&g_maps.act1ld, (__nv_bfloat16*)ctx + 2048, SEQ, 768, HDALL, 128);
    cudaFuncSetAttribute(k_mega, cudaFuncAttributeMaxDynamicSharedMemorySize, MK_SMEM);
    g_init = true;
  }
  g_ptrs.x = (const __nv_bfloat16*)d_in[0]; g_ptrs.wg = (const __nv_bfloat16*)d_in[7]; g_ptrs.wu = (const __nv_bfloat16*)d_in[8];
  g_ptrs.wo = (const __nv_bfloat16*)d_in[5]; g_ptrs.wd = (const __nv_bfloat16*)d_in[9]; g_ptrs.out = (__nv_bfloat16*)d_out;
  g_ptrs.ckv = (const __nv_bfloat16*)d_in[1]; g_ptrs.wk = (const __nv_bfloat16*)d_in[3]; g_ptrs.wv = (const __nv_bfloat16*)d_in[4];
  k_mega<<<128, 384, MK_SMEM, cudaStreamPerThread>>>(g_maps, g_ptrs);
}
```
